```python
import torch

def _softmax(x, axis=-1):
    return torch.softmax(x, dim=axis)
def _gelu(x):
    return torch.nn.functional.gelu(x, approximate="tanh")
def _silu(x):
    return torch.nn.functional.silu(x)
def _sigmoid(x):
    return torch.sigmoid(x)
def _layernorm(x, axis=-1, eps=1e-5):
    m = x.mean(dim=axis, keepdim=True)
    v = x.var(dim=axis, keepdim=True, unbiased=False)
    return (x - m) / torch.sqrt(v + eps)
def _scatter_add(tgt, idx, src, axis=0):
    return tgt.clone().index_add_(axis, idx, src)
def _segment_sum(src, seg, n):
    out = torch.zeros((n,) + src.shape[1:], dtype=src.dtype)
    return out.index_add_(0, seg, src)
def _pad(x, pw):
    flat = tuple(v for pair in reversed(pw) for v in pair)
    return torch.nn.functional.pad(x, flat)

kernel_name = 'recurrent_scan__mha_block_cached__geglu_ffn__decode'

def setup_inputs():

    _w = (lambda a: (lambda t: t.to(torch.bfloat16) if t.is_floating_point() else t)(torch.as_tensor(a)))
    def _A_setup():
        B, Sq, D = 2, 1, 512
        H, Sk, Dh = 32, 8192, 128
        return {
            "x": _w((lambda *s: torch.randn(*s, dtype=torch.bfloat16) * 0.05)(B, Sq, D)),
            "k_cache": _w((lambda *s: torch.randn(*s, dtype=torch.bfloat16) * 1.6)(B, H, Sk, Dh)),
            "v_cache": _w((lambda *s: torch.randn(*s, dtype=torch.bfloat16) * 0.2)(B, H, Sk, Dh)),
            "wq": _w((lambda *s: torch.randn(*s, dtype=torch.bfloat16) * 1.6)(D, H * Dh) * (D ** -0.5)),
            "wo": _w((lambda *s: torch.randn(*s, dtype=torch.bfloat16) * 0.2)(H * Dh, D) * ((H * Dh) ** -0.5)),
        }
    _A_in = _A_setup()

    def _B_setup():
        B, S, D, F = 2, 1, 512, 1376
        return {
            "x": _w((lambda *s: torch.randn(*s, dtype=torch.bfloat16) * 0.05)(B, S, D)),
            "w_gate": _w((lambda *s: torch.randn(*s, dtype=torch.bfloat16) * 0.1)(D, F)),
            "w_up": _w((lambda *s: torch.randn(*s, dtype=torch.bfloat16) * 0.1)(D, F)),
            "w_down": _w((lambda *s: torch.randn(*s, dtype=torch.bfloat16) * 0.1)(F, D)),
        }
    _B_in = _B_setup()

    return {
        "A_x": _A_in["x"],
        "A_k_cache": _A_in["k_cache"],
        "A_v_cache": _A_in["v_cache"],
        "A_wq": _A_in["wq"],
        "A_wo": _A_in["wo"],
        "B_x": _B_in["x"],
        "B_w_gate": _B_in["w_gate"],
        "B_w_up": _B_in["w_up"],
        "B_w_down": _B_in["w_down"],
    }

def reference(A_x, A_k_cache, A_v_cache, A_wq, A_wo, B_x, B_w_gate, B_w_up, B_w_down):
    def _A_ref(x, k_cache, v_cache, wq, wo):
        B, Sq, D = x.shape
        H, Dh = 32, 128
        q = (lambda x, *d: x.permute(*d))((x @ wq).reshape(B, Sq, H, Dh), 0, 2, 1, 3)
        scores = torch.einsum("bhqd,bhkd->bhqk", q, k_cache) * (Dh ** -0.5)
        p = _softmax(scores, axis=-1)
        o = torch.einsum("bhqk,bhkd->bhqd", p, v_cache)
        return (lambda x, *d: x.permute(*d))(o, 0, 2, 1, 3).reshape(B, Sq, H * Dh) @ wo

    def _B_ref(x, w_gate, w_up, w_down):
        return (_gelu(x @ w_gate) * (x @ w_up)) @ w_down

    x = A_x
    xn = _layernorm(x, axis=-1)
    s = _A_ref(xn, A_k_cache, A_v_cache, A_wq, A_wo)
    g = _silu(_B_ref(xn, B_w_gate, B_w_up, B_w_down))
    return x + s * g
```

```cpp
#include <cuda_runtime.h>
#include <cuda_bf16.h>
#include <stdint.h>

namespace {

constexpr int DM = 512;
constexpr int NH = 32;
constexpr int SK = 8192;
constexpr int DH = 128;
constexpr int FF = 1376;

constexpr int NATT = 128;
constexpr int NFFN = 4;
constexpr int NCTA = NATT + NFFN;
constexpr int G = 16;
constexpr int PH = G / 2;
constexpr int TK = 64;
constexpr int TILE_BYTES = TK * DH * 2;
constexpr int TPP = SK / TK / G;
constexpr int NSLOT = 12;
#define KDEPTH 3
constexpr int DEPTH = KDEPTH;
constexpr int NLOAD = 2 * PH * TPP;
constexpr int DS = DH / G;
constexpr int SPL = 32 / G;
constexpr int PSTRIDE = DS + 4;

#define KWFIRST 5
constexpr int WFIRST = KWFIRST;
constexpr int WROWS = (PH - 1 - WFIRST) * DS;
constexpr int WSLOT_ROWS = TILE_BYTES / (DM * 2);
constexpr int WSLOTS = (WROWS + WSLOT_ROWS - 1) / WSLOT_ROWS;

constexpr int NCW = 4;
constexpr int NEW = 4;
constexpr int NTHREADS = (NCW + NEW + 1) * 32;

constexpr int FMAX = 352;
constexpr int GU_PITCH = 2 * FMAX * 2 + 16;
constexpr int DN_PITCH = DM * 2 + 16;
constexpr int FSTAGE_BYTES = 32 * GU_PITCH;
constexpr int FSTAGES = 4;

constexpr int SM_P = NSLOT * TILE_BYTES;
constexpr int P_T = 136;
constexpr int SM_ML = SM_P + 2 * NCW * 4 * P_T * 4;
constexpr int SM_QS = SM_ML + 2 * NCW * 2 * 4;
constexpr int SM_XN = SM_QS + PH * 64 * 4;
constexpr int SM_RED = SM_XN + 2 * DM * 4;
constexpr int SM_BAR = SM_RED + 8 * 64 * 4;
constexpr int SM_TOTAL = SM_BAR + 64 * 8;
static_assert(FSTAGES * FSTAGE_BYTES <= NSLOT * TILE_BYTES, "ffn ring");
static_assert(2 * 2 * FMAX * 4 + 2 * FMAX * 2 <= 2 * NCW * 4 * P_T * 4, "ffn scratch");
static_assert(SM_TOTAL <= 232448, "smem");
static_assert(NCW == 4 && NEW == 4, "barrier counts");

#define PACE_TAU 670
#define PACE_OFF 1400
#define LAG1 900
#define FFN_TAU 0
#define WPACE_TAU 340
#define WDEPTH 3
constexpr float LOG2E = 1.4426950408889634f;
constexpr int SPIN_LIMIT = 1 << 22;

__device__ uint2 g_q[2][NH * DH / 2];
__device__ uint2 g_part[2 * NH][G][G][PSTRIDE];
__device__ uint2 g_fin[2][DM / 8][NATT / 2][8];
__device__ uint2 g_ffn[NFFN][2][DM];
__device__ unsigned int g_epoch[NCTA * 8];

__device__ __forceinline__ unsigned long long gtime() {
    unsigned long long t; asm volatile("mov.u64 %0, %globaltimer;" : "=l"(t)); return t;
}
#define PROF(i) do {} while (0)
#define PROF_FLUSH(mask) do {} while (0)
#define PROFV(i, v) do {} while (0)

__device__ __forceinline__ float bf16r(float x) { return __bfloat162float(__float2bfloat16_rn(x)); }
__device__ __forceinline__ float bf_lo(uint32_t u) { return __uint_as_float(u << 16); }
__device__ __forceinline__ float bf_hi(uint32_t u) { return __uint_as_float(u & 0xffff0000u); }
__device__ __forceinline__ uint32_t pack_bf16(float lo, float hi) {
    uint32_t r; asm("cvt.rn.bf16x2.f32 %0, %1, %2;" : "=r"(r) : "f"(hi), "f"(lo)); return r;
}
__device__ __forceinline__ float ex2(float x) { float r; asm("ex2.approx.ftz.f32 %0, %1;" : "=f"(r) : "f"(x)); return r; }

__device__ __forceinline__ void mbar_init(uint32_t a, uint32_t c) {
    asm volatile("mbarrier.init.shared::cta.b64 [%0], %1;" ::"r"(a), "r"(c) : "memory");
}
__device__ __forceinline__ void mbar_expect_tx(uint32_t a, uint32_t b) {
    asm volatile("mbarrier.arrive.expect_tx.shared::cta.b64 _, [%0], %1;" ::"r"(a), "r"(b) : "memory");
}
__device__ __forceinline__ void mbar_arrive(uint32_t a) {
    asm volatile("mbarrier.arrive.shared::cta.b64 _, [%0];" ::"r"(a) : "memory");
}
__device__ __forceinline__ void mbar_wait(uint32_t a, uint32_t ph) {
    uint32_t ok; int it = 0;
    do {
        asm volatile("{.reg .pred p; mbarrier.try_wait.parity.shared::cta.b64 p, [%1], %2; selp.u32 %0,1,0,p;}"
                     : "=r"(ok) : "r"(a), "r"(ph) : "memory");
        if (++it > SPIN_LIMIT) __trap();
    } while (!ok);
}
__device__ __forceinline__ bool mbar_test(uint32_t a, uint32_t ph) {
    uint32_t ok;
    asm volatile("{.reg .pred p; mbarrier.test_wait.parity.shared::cta.b64 p, [%1], %2; selp.u32 %0,1,0,p;}"
                 : "=r"(ok) : "r"(a), "r"(ph) : "memory");
    return ok;
}
__device__ __forceinline__ void bulk_load(uint32_t dst, const void* src, uint32_t bytes, uint32_t bar, uint64_t pol) {
    asm volatile("cp.async.bulk.shared::cluster.global.mbarrier::complete_tx::bytes.L2::cache_hint [%0], [%1], %2, [%3], %4;"
                 ::"r"(dst), "l"(src), "r"(bytes), "r"(bar), "l"(pol) : "memory");
}
__device__ __forceinline__ void bulk_load_nohint(uint32_t dst, const void* src, uint32_t bytes, uint32_t bar) {
    asm volatile("cp.async.bulk.shared::cluster.global.mbarrier::complete_tx::bytes [%0], [%1], %2, [%3];"
                 ::"r"(dst), "l"(src), "r"(bytes), "r"(bar) : "memory");
}
__device__ __forceinline__ void named_sync(int id, int n) { asm volatile("bar.sync %0, %1;" ::"r"(id), "r"(n) : "memory"); }

__device__ __forceinline__ void ldsm4(uint32_t (&r)[4], uint32_t a) {
    asm volatile("ldmatrix.sync.aligned.m8n8.x4.shared.b16 {%0,%1,%2,%3}, [%4];"
                 : "=r"(r[0]), "=r"(r[1]), "=r"(r[2]), "=r"(r[3]) : "r"(a) : "memory");
}
__device__ __forceinline__ void ldsm4t(uint32_t (&r)[4], uint32_t a) {
    asm volatile("ldmatrix.sync.aligned.m8n8.x4.trans.shared.b16 {%0,%1,%2,%3}, [%4];"
                 : "=r"(r[0]), "=r"(r[1]), "=r"(r[2]), "=r"(r[3]) : "r"(a) : "memory");
}
__device__ __forceinline__ void mma16816(float (&c)[4], const uint32_t (&a)[4], uint32_t b0, uint32_t b1) {
    asm volatile("mma.sync.aligned.m16n8k16.row.col.f32.bf16.bf16.f32 {%0,%1,%2,%3}, {%4,%5,%6,%7}, {%8,%9}, {%0,%1,%2,%3};"
                 : "+f"(c[0]), "+f"(c[1]), "+f"(c[2]), "+f"(c[3])
                 : "r"(a[0]), "r"(a[1]), "r"(a[2]), "r"(a[3]), "r"(b0), "r"(b1));
}

__device__ __forceinline__ uint4 ld_ll(const void* p) {
    uint4 v;
    asm volatile("ld.relaxed.gpu.global.v4.u32 {%0,%1,%2,%3}, [%4];"
                 : "=r"(v.x), "=r"(v.y), "=r"(v.z), "=r"(v.w) : "l"(p) : "memory");
    return v;
}
__device__ __forceinline__ void st_ll2(void* p, uint32_t a, uint32_t tag) {
    asm volatile("st.relaxed.gpu.global.v2.u32 [%0], {%1,%2};" ::"l"(p), "r"(a), "r"(tag) : "memory");
}
__device__ __forceinline__ void st_ll4(void* p, uint32_t a, uint32_t b, uint32_t tag) {
    asm volatile("st.relaxed.gpu.global.v4.u32 [%0], {%1,%2,%3,%2};" ::"l"(p), "r"(a), "r"(tag), "r"(b) : "memory");
}
__device__ __forceinline__ void ld_ll_missing(uint4& v, const void* p, uint32_t tag) {
    asm volatile("{.reg .pred q; setp.ne.u32 q, %1, %5; setp.ne.or.u32 q, %3, %5, q;\n\t"
                 "@q ld.relaxed.gpu.global.v4.u32 {%0,%1,%2,%3}, [%4];}"
                 : "+r"(v.x), "+r"(v.y), "+r"(v.z), "+r"(v.w) : "l"(p), "r"(tag) : "memory");
}
__device__ __forceinline__ void st_u32_if(void* p, uint32_t v, bool on) {
    asm volatile("{.reg .pred q; setp.ne.u32 q, %2, 0; @q st.global.u32 [%0], %1;}" ::"l"(p), "r"(v), "r"((uint32_t)on) : "memory");
}
__device__ __forceinline__ bool ll_ok(const uint4& v, uint32_t tag) { return v.y == tag && v.w == tag; }

__device__ __forceinline__ float warp_max(float v) {
    int i = __float_as_int(v);
    i = i >= 0 ? i : (i ^ 0x7fffffff);
    i = __reduce_max_sync(0xffffffffu, i);
    i = i >= 0 ? i : (i ^ 0x7fffffff);
    return __int_as_float(i);
}

__device__ __forceinline__ float rcp_approx(float x) { float r; asm("rcp.approx.ftz.f32 %0, %1;" : "=f"(r) : "f"(x)); return r; }

__device__ __noinline__ void layernorm_row(uint4 u0, uint4 u1, uint32_t* dst, int lane) {
    uint32_t w[8] = {u0.x, u0.y, u0.z, u0.w, u1.x, u1.y, u1.z, u1.w};
    float y[16];
    float s = 0.f;
#pragma unroll
    for (int i = 0; i < 8; i++) { y[2 * i] = bf_lo(w[i]); y[2 * i + 1] = bf_hi(w[i]); s += y[2 * i] + y[2 * i + 1]; }
#pragma unroll
    for (int o = 16; o > 0; o >>= 1) s += __shfl_xor_sync(0xffffffffu, s, o);
    const float mean = s * (1.f / DM);
    float v = 0.f;
#pragma unroll
    for (int i = 0; i < 16; i++) { const float d = y[i] - mean; v = fmaf(d, d, v); }
#pragma unroll
    for (int o = 16; o > 0; o >>= 1) v += __shfl_xor_sync(0xffffffffu, v, o);
    const float mb = bf16r(mean);
    float sd;
    asm("sqrt.approx.f32 %0, %1;" : "=f"(sd) : "f"(bf16r(bf16r(v * (1.f / DM)) + 1e-5f)));
    const float inv = rcp_approx(bf16r(sd));
#pragma unroll
    for (int i = 0; i < 8; i++) {
        const uint32_t d = pack_bf16(y[2 * i] - mb, y[2 * i + 1] - mb);
        w[i] = pack_bf16(bf_lo(d) * inv, bf_hi(d) * inv);
    }
    *(uint4*)(dst + 4 * lane) = make_uint4(w[0], w[1], w[2], w[3]);
    *(uint4*)(dst + 128 + 4 * lane) = make_uint4(w[4], w[5], w[6], w[7]);
}

__device__ __noinline__ float4 wo_project(float4 acc, uint32_t w, uint32_t o, int rows) {
#pragma unroll 1
    for (int r = 0; r < rows; r += 4) {
        float4 ov;
        uint32_t a[4], b[4];
        asm volatile("ld.shared.v4.f32 {%0,%1,%2,%3}, [%4];" : "=f"(ov.x), "=f"(ov.y), "=f"(ov.z), "=f"(ov.w) : "r"(o + 4 * r));
#pragma unroll
        for (int i = 0; i < 4; i++) {
            asm volatile("ld.shared.u32 %0, [%1];" : "=r"(a[i]) : "r"(w + (r + i) * (DM * 2)));
            asm volatile("ld.shared.u32 %0, [%1];" : "=r"(b[i]) : "r"(w + (r + i) * (DM * 2) + DM));
        }
        const float of[4] = {ov.x, ov.y, ov.z, ov.w};
#pragma unroll
        for (int i = 0; i < 4; i++) {
            acc.x = fmaf(of[i], bf_lo(a[i]), acc.x); acc.y = fmaf(of[i], bf_hi(a[i]), acc.y);
            acc.z = fmaf(of[i], bf_lo(b[i]), acc.z); acc.w = fmaf(of[i], bf_hi(b[i]), acc.w);
        }
    }
    return acc;
}

__device__ __noinline__ void ffn_cta(const __nv_bfloat16* __restrict__ x, const __nv_bfloat16* __restrict__ wg,
                                     const __nv_bfloat16* __restrict__ wu, const __nv_bfloat16* __restrict__ wd);
__device__ __noinline__ void attn_workers(const __nv_bfloat16* __restrict__ x, const __nv_bfloat16* __restrict__ wq,
                                          const __nv_bfloat16* __restrict__ wo, __nv_bfloat16* __restrict__ out);

__global__ void __launch_bounds__(NTHREADS, 1)
fused_decode_kernel(const __nv_bfloat16* __restrict__ x, const __nv_bfloat16* __restrict__ kc,
                    const __nv_bfloat16* __restrict__ vc, const __nv_bfloat16* __restrict__ wq,
                    const __nv_bfloat16* __restrict__ wo, const __nv_bfloat16* __restrict__ wg,
                    const __nv_bfloat16* __restrict__ wu, const __nv_bfloat16* __restrict__ wd,
                    __nv_bfloat16* __restrict__ out) {
    extern __shared__ __align__(1024) unsigned char smem[];
    const uint32_t sb = (uint32_t)__cvta_generic_to_shared(smem);
    const int cta = blockIdx.x;
    const uint32_t bar_full = sb + SM_BAR, bar_empty = bar_full + 8 * NSLOT;
    const uint32_t bar_q = bar_empty + 8 * NSLOT + 32;
    volatile int* progress = (volatile int*)(smem + SM_BAR + 60 * 8);
    const int grp = cta / G, rk = cta % G;

    if (__builtin_expect(threadIdx.x < 32 && cta < NATT, 1)) {
        uint64_t pol = 0;
        const size_t base = ((size_t)grp * PH * SK + (size_t)rk * TK) * DH * 2;
        const char* src0 = (const char*)kc + base;
        const char* src1 = (const char*)vc + base;
        uint32_t t0 = 0;
        if (threadIdx.x == 0) {
            t0 = (uint32_t)gtime();
            PROF(0);
            mbar_init(bar_full, 1);
            asm volatile("fence.mbarrier_init.release.cluster;" ::: "memory");
            asm volatile("fence.proxy.async.shared::cta;" ::: "memory");
            asm volatile("createpolicy.fractional.L2::evict_first.b64 %0, 1.0;" : "=l"(pol));
            mbar_expect_tx(bar_full, TILE_BYTES);
            bulk_load(sb, src0, TILE_BYTES, bar_full, pol);
            { const char* nx = src0 + G * TILE_BYTES; src0 = src1; src1 = nx; }
            PROF(11);
#pragma unroll 1
            for (int i = 1; i < NSLOT; i++) mbar_init(bar_full + 8 * i, 1);
#pragma unroll 1
            for (int i = 0; i < NSLOT + 4; i++) mbar_init(bar_empty + 8 * i, 4);
            mbar_init(bar_q, 1); mbar_init(bar_q + 8, NEW); mbar_init(bar_q + 16, 1); mbar_init(bar_q + 24, NCW);
            *progress = 0;
            asm volatile("fence.mbarrier_init.release.cluster;" ::: "memory");
            asm volatile("fence.proxy.async.shared::cta;" ::: "memory");
        }
        __syncwarp();
        asm volatile("bar.arrive 0, %0;" ::"n"(NTHREADS) : "memory");
        if (threadIdx.x == 0) {
            int st = 1, ph = 1;
            int ws = 0, wph = 0;
            int landed = 0;
#pragma unroll 1
            for (int i = 1; i < NLOAD; i++) {
                for (int it = 0;; it++) {
                    const int lag = (int)((uint32_t)gtime() - t0) - (i * PACE_TAU + PACE_OFF);
                    if (lag >= 0 && i - landed < DEPTH + (lag > LAG1)) break;
                    if (landed < i && mbar_test(bar_full + 8 * ws, wph)) {
                        if (landed == 0) PROF(12);
                        ++landed;
                        if (++ws == NSLOT) { ws = 0; wph ^= 1; }
                    }
                    if (it > SPIN_LIMIT) __trap();
                }
                mbar_wait(bar_empty + 8 * st, ph);
                mbar_expect_tx(bar_full + 8 * st, TILE_BYTES);
                bulk_load(sb + st * TILE_BYTES, src0, TILE_BYTES, bar_full + 8 * st, pol);
                const char* nx = src0 + G * TILE_BYTES; src0 = src1; src1 = nx;
                if (++st == NSLOT) { st = 0; ph ^= 1; }
            }
            PROF(1);
            const char* wsrc = (const char*)(wo + (size_t)(((grp % (NH / PH)) * PH + WFIRST) * DH + rk * DS) * DM);
#pragma unroll 1
            for (int i = 0; i < WSLOTS; i++) {
                while (NLOAD + i - landed >= WDEPTH) {
                    mbar_wait(bar_full + 8 * ws, wph);
                    ++landed;
                    if (++ws == NSLOT) { ws = 0; wph ^= 1; }
                }
                while ((uint32_t)gtime() - t0 < (uint32_t)(NLOAD * PACE_TAU + PACE_OFF + i * WPACE_TAU)) {}
                mbar_wait(bar_empty + 8 * st, ph);
                const int np = min(WSLOT_ROWS, WROWS - i * WSLOT_ROWS) / DS;
                mbar_expect_tx(bar_full + 8 * st, np * DS * DM * 2);
#pragma unroll 1
                for (int k = 0; k < np; k++) {
                    bulk_load_nohint(sb + st * TILE_BYTES + k * (DS * DM * 2), wsrc, DS * DM * 2, bar_full + 8 * st);
                    wsrc += DH * DM * 2;
                }
                if (++st == NSLOT) { st = 0; ph ^= 1; }
            }
            PROF_FLUSH(0x1803);
        }
        return;
    }
    if (cta >= NATT) ffn_cta(x, wg, wu, wd);
    else attn_workers(x, wq, wo, out);
}

__device__ __noinline__ void attn_workers(const __nv_bfloat16* __restrict__ x, const __nv_bfloat16* __restrict__ wq,
                                          const __nv_bfloat16* __restrict__ wo, __nv_bfloat16* __restrict__ out) {
    extern __shared__ __align__(1024) unsigned char smem[];
    const uint32_t sb = (uint32_t)__cvta_generic_to_shared(smem);
    const int cta = blockIdx.x;
    const uint32_t bar_full = sb + SM_BAR, bar_empty = bar_full + 8 * NSLOT;
    const uint32_t bar_pfull = bar_empty + 8 * NSLOT, bar_pempty = bar_pfull + 16, bar_q = bar_pempty + 16;
    volatile int* progress = (volatile int*)(smem + SM_BAR + 60 * 8);
    const int grp = cta / G, rk = cta % G;
    {
        const int tid = threadIdx.x - 32, warp = tid >> 5, lane = tid & 31;
        const int g = lane >> 2, t = lane & 3;
        uint32_t* xb = (uint32_t*)(smem + SM_XN);
        float* red = (float*)(smem + SM_RED);
        uint4 wv[8];
        uint4 u0 = make_uint4(0, 0, 0, 0), u1 = u0;
        if (warp < 2) { u0 = __ldg((const uint4*)(x + warp * DM) + lane); u1 = __ldg((const uint4*)(x + warp * DM + 256) + lane); }
        {
            const uint4* src = (const uint4*)(wq + (size_t)(tid >> 2) * (NH * DH) + cta * 32 + (tid & 3) * 8);
#pragma unroll
            for (int i = 0; i < 8; i++) wv[i] = __ldg(src + (size_t)i * 64 * (NH * DH / 8));
        }
        if (warp == NCW) st_ll2(&g_q[lane >> 4][cta * 16 + (lane & 15)], 0u, 0u);
        uint32_t tag;
        asm volatile("ld.relaxed.gpu.global.u32 %0, [%1];" : "=r"(tag) : "l"(&g_epoch[cta * 8]) : "memory");
        if (warp < 2) layernorm_row(u0, u1, xb + warp * 256, lane);
        named_sync(0, NTHREADS);
        tag += 1;
        if (tid == 0) PROF(8);
        {
            float a0[8], a1[8];
#pragma unroll
            for (int c = 0; c < 8; c++) { a0[c] = 0.f; a1[c] = 0.f; }
#pragma unroll
            for (int i = 0; i < 8; i++) {
                const float x0 = __bfloat162float(((const __nv_bfloat16*)xb)[(tid >> 2) + 64 * i]);
                const float x1 = __bfloat162float(((const __nv_bfloat16*)xb)[DM + (tid >> 2) + 64 * i]);
                const uint32_t w[4] = {wv[i].x, wv[i].y, wv[i].z, wv[i].w};
#pragma unroll
                for (int c = 0; c < 4; c++) {
                    const float lo = bf_lo(w[c]), hi = bf_hi(w[c]);
                    a0[2 * c] = fmaf(x0, lo, a0[2 * c]); a0[2 * c + 1] = fmaf(x0, hi, a0[2 * c + 1]);
                    a1[2 * c] = fmaf(x1, lo, a1[2 * c]); a1[2 * c + 1] = fmaf(x1, hi, a1[2 * c + 1]);
                }
            }
            const bool b4 = lane & 16, b3 = lane & 8, b2 = lane & 4;
            float r8[8], r4[4], r2[2];
#pragma unroll
            for (int c = 0; c < 8; c++) {
                const float keep = b4 ? a1[c] : a0[c], send = b4 ? a0[c] : a1[c];
                r8[c] = keep + __shfl_xor_sync(0xffffffffu, send, 16);
            }
#pragma unroll
            for (int c = 0; c < 4; c++) {
                const float keep = b3 ? r8[4 + c] : r8[c], send = b3 ? r8[c] : r8[4 + c];
                r4[c] = keep + __shfl_xor_sync(0xffffffffu, send, 8);
            }
#pragma unroll
            for (int c = 0; c < 2; c++) {
                const float keep = b2 ? r4[2 + c] : r4[c], send = b2 ? r4[c] : r4[2 + c];
                r2[c] = keep + __shfl_xor_sync(0xffffffffu, send, 4);
            }
            const int col = (b4 ? 32 : 0) + t * 8 + (b3 ? 4 : 0) + (b2 ? 2 : 0);
            *(float2*)&red[warp * 64 + col] = make_float2(r2[0], r2[1]);
        }
        named_sync(1, (NCW + NEW) * 32);

        if (warp < NCW) {
            const int r = lane & 7, mi = lane >> 3;
            uint32_t koff[4], voff[4];
#pragma unroll
            for (int j = 0; j < 4; j++) {
                koff[j] = sb + (warp * 16 + r + 8 * (mi & 1)) * 256 + (((2 * j + (mi >> 1)) ^ r) << 4);
                voff[j] = sb + (warp * 16 + r + 8 * (mi >> 1)) * 256 + (((2 * j + (mi & 1)) ^ r) << 4);
            }
            const bool owner = (t == (g >> 1));
            const bool odd = g & 1;
            const uint32_t* qs = (const uint32_t*)(smem + SM_QS);
            float* P = (float*)(smem + SM_P);
            float* ml = (float*)(smem + SM_ML);
            int st = 0, ph = 0;
            wo_project(make_float4(0.f, 0.f, 0.f, 0.f), sb + 4 * tid, sb + SM_XN, 4);
            mbar_wait(bar_q, 0);
            if (tid == 0) PROF(2);
            for (int j = 0; j < PH; j++) {
                if (j == 1) mbar_wait(bar_q + 8, 0);
                uint32_t qb[8][2];
#pragma unroll
                for (int k = 0; k < 8; k++) {
                    qb[k][0] = qs[j * 64 + (((2 * k) ^ g) << 2) + t];
                    qb[k][1] = qs[j * 64 + (((2 * k + 1) ^ g) << 2) + t];
                }
                float acc[8][4];
#pragma unroll
                for (int k = 0; k < 8; k++) { acc[k][0] = acc[k][1] = acc[k][2] = acc[k][3] = 0.f; }
                float m = -INFINITY, l = 0.f;
#pragma unroll 1
                for (int tt = 0; tt < TPP; tt++) {
                    uint32_t a[8][4];
                    mbar_wait(bar_full + 8 * st, ph);
                    {
                        const uint32_t so = st * TILE_BYTES;
#pragma unroll
                        for (int k = 0; k < 8; k++) ldsm4(a[k], koff[k & 3] + so + (k >> 2) * 128);
                    }
                    float c0[4] = {0.f, 0.f, 0.f, 0.f}, c1[4] = {0.f, 0.f, 0.f, 0.f};
#pragma unroll
                    for (int k = 0; k < 8; k += 2) {
                        mma16816(c0, a[k], qb[k][0], qb[k][1]);
                        mma16816(c1, a[k + 1], qb[k + 1][0], qb[k + 1][1]);
                    }
                    __syncwarp();
                    if (lane == 0) mbar_arrive(bar_empty + 8 * st);
                    ++st;
                    float s0 = odd ? (c0[1] + c1[1]) : (c0[0] + c1[0]);
                    float s1 = odd ? (c0[3] + c1[3]) : (c0[2] + c1[2]);
                    s0 = bf16r(bf16r(s0) * 0.08838834764831845f);
                    s1 = bf16r(bf16r(s1) * 0.08838834764831845f);
                    if (!owner) { s0 = -INFINITY; s1 = -INFINITY; }
                    const float mx = fmaxf(s0, s1);
                    if (__any_sync(0xffffffffu, mx > m)) {
                        const float mn = warp_max(mx);
                        const float alpha = ex2((m - mn) * LOG2E);
                        m = mn;
                        l *= alpha;
#pragma unroll
                        for (int k = 0; k < 8; k++) { acc[k][0] *= alpha; acc[k][1] *= alpha; acc[k][2] *= alpha; acc[k][3] *= alpha; }
                    }
                    const float p0 = ex2((s0 - m) * LOG2E), p1 = ex2((s1 - m) * LOG2E);
                    l += p0 + p1;
                    const uint32_t b0 = odd ? pack_bf16(0.f, p0) : pack_bf16(p0, 0.f);
                    const uint32_t b1 = odd ? pack_bf16(0.f, p1) : pack_bf16(p1, 0.f);
                    if (tt == TPP - 1) {
#pragma unroll
                        for (int o = 16; o > 0; o >>= 1) l += __shfl_xor_sync(0xffffffffu, l, o);
                        if (j >= 2) mbar_wait(bar_pempty + 8 * (j & 1), ((j >> 1) - 1) & 1);
                        if (lane == 0) { ml[((j & 1) * NCW + warp) * 2] = m; ml[((j & 1) * NCW + warp) * 2 + 1] = l; }
                    }
                    mbar_wait(bar_full + 8 * st, ph);
                    {
                        const uint32_t so = st * TILE_BYTES;
#pragma unroll
                        for (int k = 0; k < 8; k++) ldsm4t(a[k], voff[k & 3] + so + (k >> 2) * 128);
                    }
#pragma unroll
                    for (int k = 0; k < 8; k++) mma16816(acc[k], a[k], b0, b1);
                    __syncwarp();
                    if (lane == 0) mbar_arrive(bar_empty + 8 * st);
                    if (++st == NSLOT) { st = 0; ph ^= 1; }
                    if (tt == 1 && tid == 0) *progress = j;
                }
                float* Pw = P + (((j & 1) * NCW + warp) * 4 + t) * P_T + g;
#pragma unroll
                for (int k = 0; k < 8; k++) {
                    Pw[((k ^ t) * 2) * 8] = acc[k][0] + acc[k][3];
                    Pw[((k ^ t) * 2 + 1) * 8] = acc[k][2] + acc[k][1];
                }
                __syncwarp();
                if (lane == 0) mbar_arrive(bar_pfull + 8 * (j & 1));
            }
            if (tid == 0) PROF(3);
            float4 sp = make_float4(0.f, 0.f, 0.f, 0.f);
            mbar_wait(bar_q + 16, 0);
#pragma unroll 1
            for (int i = 0; i < WSLOTS; i++) {
                mbar_wait(bar_full + 8 * st, ph);
                sp = wo_project(sp, sb + st * TILE_BYTES + 4 * tid, sb + SM_XN + i * WSLOT_ROWS * 4,
                                min(WSLOT_ROWS, WROWS - i * WSLOT_ROWS));
                if (++st == NSLOT) { st = 0; ph ^= 1; }
            }
            *(float4*)&red[4 * tid] = sp;
            __syncwarp();
            if (lane == 0) mbar_arrive(bar_q + 24);
            if (tid == 0) { PROF(9); PROF_FLUSH(0x30c); }
            return;
        }

        const int et = tid - NCW * 32;
        if (warp == NCW) {
            float2 s = make_float2(0.f, 0.f);
#pragma unroll
            for (int w = 0; w < NCW + NEW; w++) { const float2 v = *(const float2*)&red[w * 64 + 2 * lane]; s.x += v.x; s.y += v.y; }
            st_ll2(&g_q[lane >> 4][cta * 16 + (lane & 15)], pack_bf16(s.x, s.y), tag);
            if (lane == 0) PROF(10);
        }
        const int bb = grp / (NH / PH);
        const int h0 = (grp % (NH / PH)) * PH;
        {
            uint32_t* qs = (uint32_t*)(smem + SM_QS);
            const uint2* src = &g_q[bb][h0 * 64];
            if (warp == NCW + 1) {
                uint4 v; int it = 0;
                do { v = ld_ll(src + 2 * lane); if (++it > SPIN_LIMIT) __trap(); } while (!ll_ok(v, tag));
                *(uint2*)&qs[2 * lane] = make_uint2(v.x, v.z);
                __syncwarp();
                if (lane == 0) mbar_arrive(bar_q);
            }
            mbar_wait(bar_q, 0);
            __nanosleep(2000);
            for (int i = 32 + et; i < PH * 32; i += NEW * 32) {
                uint4 v; int it = 0;
                while (true) {
                    v = ld_ll(src + 2 * i);
                    if (ll_ok(v, tag)) break;
                    if (++it > SPIN_LIMIT) __trap();
                    __nanosleep(500);
                }
                *(uint2*)&qs[2 * i] = make_uint2(v.x, v.z);
            }
            __syncwarp();
            if (lane == 0) mbar_arrive(bar_q + 8);
        }
        const float* P = (const float*)(smem + SM_P);
        const float* ml = (const float*)(smem + SM_ML);
        float sacc[4] = {0.f, 0.f, 0.f, 0.f};
        float gate0 = 0.f, gate1 = 0.f, xr0 = 0.f, xr1 = 0.f;
#pragma unroll 1
        for (int j = 0; j < PH; j++) {
            const int head = grp * PH + j;
            const bool last = (j == PH - 1);
            uint32_t w0[DS], w1[DS];
#pragma unroll
            for (int i = 0; i < DS; i++) { w0[i] = 0u; w1[i] = 0u; }
            if (last || j < WFIRST) {
                const uint32_t* src = (const uint32_t*)(wo + (size_t)((h0 + j) * DH + rk * DS) * DM) + et;
#pragma unroll
                for (int i = 0; i < DS; i++) { w0[i] = __ldg(src + i * (DM / 2)); w1[i] = __ldg(src + i * (DM / 2) + DM / 4); }
            }
            if (last && warp == NCW) {
                const int fb = cta / (NATT / 2), col = (cta % (NATT / 2)) * 8 + 2 * t;
                uint4 v; int it = 0;
                while (true) {
                    v = ld_ll(&g_ffn[g & 3][fb][col]);
                    if (ll_ok(v, tag)) break;
                    if (++it > SPIN_LIMIT) __trap();
                    __nanosleep(500);
                }
                float f0 = __uint_as_float(v.x), f1 = __uint_as_float(v.z);
                f0 += __shfl_xor_sync(0xffffffffu, f0, 4); f1 += __shfl_xor_sync(0xffffffffu, f1, 4);
                f0 += __shfl_xor_sync(0xffffffffu, f0, 8); f1 += __shfl_xor_sync(0xffffffffu, f1, 8);
                f0 = bf16r(f0); f1 = bf16r(f1);
                gate0 = bf16r(f0 * rcp_approx(1.f + ex2(-f0 * LOG2E))); gate1 = bf16r(f1 * rcp_approx(1.f + ex2(-f1 * LOG2E)));
                const uint32_t xu = __ldg((const uint32_t*)(x + fb * DM + col));
                xr0 = bf_lo(xu); xr1 = bf_hi(xu);
            }
            uint2* dst_o = &g_part[head][et / DS][rk][et % DS];
            uint2* dst_ml = &g_part[head][(et >> 1) % G][rk][DS + 2 * (et & 1)];
            const uint2* src_o = &g_part[head][rk][lane / SPL][(lane % SPL) * 4];
            const uint2* src_ml = &g_part[head][rk][lane / SPL][DS];
            uint2* dst_fin = &g_fin[bb][et >> 2][cta % (NATT / 2)][2 * (et & 3)];
            float wf[DS][4];
#pragma unroll
            for (int i = 0; i < DS; i++) {
                wf[i][0] = bf_lo(w0[i]); wf[i][1] = bf_hi(w0[i]); wf[i][2] = bf_lo(w1[i]); wf[i][3] = bf_hi(w1[i]);
                asm volatile("" : "+f"(wf[i][0]), "+f"(wf[i][1]), "+f"(wf[i][2]), "+f"(wf[i][3]));
            }
            asm volatile("" : "+l"(dst_o), "+l"(dst_ml), "+l"(src_o), "+l"(src_ml), "+l"(dst_fin));
            mbar_wait(bar_pfull + 8 * (j & 1), (j >> 1) & 1);
            if (j == PH - 1 && et == 0) PROF(4);
            {
                const float* mlj = ml + (j & 1) * NCW * 2;
                float M = mlj[0];
#pragma unroll
                for (int w = 1; w < NCW; w++) M = fmaxf(M, mlj[2 * w]);
                float o = 0.f, L = 0.f;
#pragma unroll
                for (int w = 0; w < NCW; w++) {
                    const float sc = ex2((mlj[2 * w] - M) * LOG2E);
                    const float* Pw = P + ((j & 1) * NCW + w) * 4 * P_T + et;
                    o = fmaf(sc, (Pw[0] + Pw[P_T]) + (Pw[2 * P_T] + Pw[3 * P_T]), o);
                    L = fmaf(sc, mlj[2 * w + 1], L);
                }
                st_ll2(dst_o, __float_as_uint(o), tag);
                if (et < 2 * G) st_ll4(dst_ml, __float_as_uint(M), __float_as_uint(L), tag);
                __syncwarp();
                if (lane == 0) mbar_arrive(bar_pempty + 8 * (j & 1));
            }
            if (!last) {
                int it = 0;
                while (*progress <= j) { __nanosleep(250); if (++it > SPIN_LIMIT) __trap(); }
            }
            float v[4], inv;
            {
                uint4 ua = make_uint4(0u, 0u, 0u, 0u), ub = ua, um = ua; int it = 0;
                ld_ll_missing(ua, src_o, tag); ld_ll_missing(ub, src_o + 2, tag); ld_ll_missing(um, src_ml, tag);
                if (last) {
                    mbar_wait(bar_q + 24, 0);
                    const float4 sp = *(const float4*)&red[4 * et];
                    sacc[0] += sp.x; sacc[1] += sp.y; sacc[2] += sp.z; sacc[3] += sp.w;
                }
                while (true) {
                    const uint32_t bad = ((ua.y ^ tag) | (ua.w ^ tag)) | ((ub.y ^ tag) | (ub.w ^ tag)) | ((um.y ^ tag) | (um.w ^ tag));
                    if (!__any_sync(0xffffffffu, bad != 0)) break;
                    if (++it > SPIN_LIMIT) __trap();
                    if (!last) __nanosleep(500);
                    ld_ll_missing(ua, src_o, tag); ld_ll_missing(ub, src_o + 2, tag); ld_ll_missing(um, src_ml, tag);
                }
                if (j == PH - 1 && et == 0) PROF(5);
                const float Ms = __uint_as_float(um.x);
                const float Mg = warp_max(Ms);
                const float sc = ex2((Ms - Mg) * LOG2E);
                float L = sc * __uint_as_float(um.z);
                v[0] = sc * __uint_as_float(ua.x); v[1] = sc * __uint_as_float(ua.z);
                v[2] = sc * __uint_as_float(ub.x); v[3] = sc * __uint_as_float(ub.z);
#pragma unroll
                for (int o = SPL; o < 32; o <<= 1) {
                    L += __shfl_xor_sync(0xffffffffu, L, o);
#pragma unroll
                    for (int i = 0; i < 4; i++) v[i] += __shfl_xor_sync(0xffffffffu, v[i], o);
                }
                inv = rcp_approx(L);
            }
            {
                float y[4] = {0.f, 0.f, 0.f, 0.f};
#pragma unroll
                for (int i = 0; i < DS; i++) {
                    const float o = __shfl_sync(0xffffffffu, v[i & 3], i >> 2);
#pragma unroll
                    for (int c = 0; c < 4; c++) y[c] = fmaf(o, wf[i][c], y[c]);
                }
#pragma unroll
                for (int c = 0; c < 4; c++) sacc[c] = fmaf(y[c], inv, sacc[c]);
            }
            if (last) {
                st_ll4(dst_fin, __float_as_uint(sacc[0]), __float_as_uint(sacc[1]), tag);
                st_ll4(dst_fin + 32 * (NATT / 2) * 8, __float_as_uint(sacc[2]), __float_as_uint(sacc[3]), tag);
            }
            if (!last && j >= WFIRST && warp == NCW) {
                if (lane < SPL) *(float4*)(smem + SM_XN + ((j - WFIRST) * DS + lane * 4) * 4) =
                    make_float4(bf16r(v[0] * inv), bf16r(v[1] * inv), bf16r(v[2] * inv), bf16r(v[3] * inv));
                __syncwarp();
                if (j == PH - 2 && lane == 0) mbar_arrive(bar_q + 16);
            }
            if (j == PH - 2) {
                st_ll2(&g_part[head + 1][et / DS][rk][et % DS], 0u, 0u);
                if (et < 2 * G) st_ll4(&g_part[head + 1][et >> 1][rk][DS + 2 * (et & 1)], 0u, 0u, 0u);
                st_ll4(dst_fin, 0u, 0u, 0u);
                st_ll4(dst_fin + 32 * (NATT / 2) * 8, 0u, 0u, 0u);
            }
            if (warp == NCW) {
                if (last && lane == 0) PROF(6);
                const int fb = cta / (NATT / 2), cg = cta % (NATT / 2);
                const uint2* src = &g_fin[fb][cg][g][2 * t];
                uint4 u[8]; int it = 0;
                const uint32_t t_init = last ? 0u : tag;
#pragma unroll
                for (int i = 0; i < 8; i++) u[i] = make_uint4(0u, t_init, 0u, t_init);
                while (true) {
                    if (last && lane == 0) PROF(13);
#pragma unroll
                    for (int i = 0; i < 8; i++) ld_ll_missing(u[i], src + i * 64, tag);
                    uint32_t bad = 0;
#pragma unroll
                    for (int i = 0; i < 8; i++) bad |= (u[i].y ^ tag) | (u[i].w ^ tag);
                    if (!__any_sync(0xffffffffu, bad != 0)) break;
                    if (++it > SPIN_LIMIT) __trap();
                }
                if (last && lane == 0) { PROF(14); PROFV(15, it); }
                float s0 = ((__uint_as_float(u[0].x) + __uint_as_float(u[1].x)) + (__uint_as_float(u[2].x) + __uint_as_float(u[3].x))) +
                           ((__uint_as_float(u[4].x) + __uint_as_float(u[5].x)) + (__uint_as_float(u[6].x) + __uint_as_float(u[7].x)));
                float s1 = ((__uint_as_float(u[0].z) + __uint_as_float(u[1].z)) + (__uint_as_float(u[2].z) + __uint_as_float(u[3].z))) +
                           ((__uint_as_float(u[4].z) + __uint_as_float(u[5].z)) + (__uint_as_float(u[6].z) + __uint_as_float(u[7].z)));
#pragma unroll
                for (int o = 4; o < 32; o <<= 1) { s0 += __shfl_xor_sync(0xffffffffu, s0, o); s1 += __shfl_xor_sync(0xffffffffu, s1, o); }
                const float o0 = xr0 + bf16r(bf16r(s0) * gate0), o1 = xr1 + bf16r(bf16r(s1) * gate1);
                st_u32_if(out + fb * DM + cg * 8 + 2 * t, pack_bf16(o0, o1), last && lane < 4);
                st_u32_if(&g_epoch[cta * 8], tag, last && lane == 0);
                if (last && lane == 0) { PROF(7); PROF_FLUSH(0xe4f0); }
            }
        }
        return;
    }

}

__device__ __noinline__ void ffn_cta(const __nv_bfloat16* __restrict__ x, const __nv_bfloat16* __restrict__ wg,
                                     const __nv_bfloat16* __restrict__ wu, const __nv_bfloat16* __restrict__ wd) {
    extern __shared__ __align__(1024) unsigned char smem[];
    const uint32_t sb = (uint32_t)__cvta_generic_to_shared(smem);
    const int tid = threadIdx.x, warp = tid >> 5, lane = tid & 31;
    const int cta = blockIdx.x;
    const int g = lane >> 2, t = lane & 3;
    const uint32_t bar_full = sb + SM_BAR, bar_empty = bar_full + 8 * NSLOT;
    const int fc = cta - NATT;
    const int f0 = fc * FMAX;
    const int nf = (fc == NFFN - 1) ? (FF - f0) : FMAX;
    const int ndn = nf / 32;
    if (warp == NCW + NEW) {
        uint64_t pol;
        asm volatile("createpolicy.fractional.L2::evict_first.b64 %0, 1.0;" : "=l"(pol));
        if (lane == 0) {
            PROF(0);
            for (int i = 0; i < FSTAGES; i++) { mbar_init(bar_full + 8 * i, 1); mbar_init(bar_empty + 8 * i, NCW + NEW); }
            asm volatile("fence.mbarrier_init.release.cluster;" ::: "memory");
            asm volatile("fence.proxy.async.shared::cta;" ::: "memory");
        }
        __syncthreads();
        int st = 0, ph = 1;
        const uint32_t t0 = (uint32_t)gtime();
        for (int i = 0; i < 16 + ndn; i++) {
            while ((uint32_t)gtime() - t0 < (uint32_t)(i * FFN_TAU)) {}
            mbar_wait(bar_empty + 8 * st, ph);
            const uint32_t dst = sb + st * FSTAGE_BYTES;
            if (i < 16) {
                if (lane == 0) mbar_expect_tx(bar_full + 8 * st, 32 * 2 * nf * 2);
                __syncwarp();
                const size_t off = (size_t)(i * 32 + lane) * FF + f0;
                bulk_load(dst + lane * GU_PITCH, wg + off, nf * 2, bar_full + 8 * st, pol);
                bulk_load(dst + lane * GU_PITCH + FMAX * 2, wu + off, nf * 2, bar_full + 8 * st, pol);
            } else {
                if (lane == 0) mbar_expect_tx(bar_full + 8 * st, 32 * DM * 2);
                __syncwarp();
                bulk_load(dst + lane * DN_PITCH, wd + (size_t)(f0 + (i - 16) * 32 + lane) * DM, DM * 2, bar_full + 8 * st, pol);
            }
            if (++st == FSTAGES) { st = 0; ph ^= 1; }
        }
        return;
    }
    {
        uint32_t* xb = (uint32_t*)(smem + SM_XN);
        float* pre = (float*)(smem + SM_P);
        uint32_t* hb = (uint32_t*)(pre + 2 * 2 * FMAX);
        const uint32_t tag = *(volatile unsigned int*)&g_epoch[cta * 8] + 1;
        if (warp < 2) {
            const uint4 u0 = __ldg((const uint4*)(x + warp * DM) + lane), u1 = __ldg((const uint4*)(x + warp * DM + 256) + lane);
            layernorm_row(u0, u1, xb + warp * 256, lane);
        }
        __syncthreads();
        const int r = lane & 7, mi = lane >> 3;
        const int mt_half = nf / 16;
        int st = 0, ph = 0;
        float acc[6][4];
#pragma unroll
        for (int k = 0; k < 6; k++) { acc[k][0] = acc[k][1] = acc[k][2] = acc[k][3] = 0.f; }
        int cb[6];
#pragma unroll
        for (int k = 0; k < 6; k++) {
            const int mt = warp + 8 * k;
            cb[k] = mt < mt_half ? mt * 32 : (mt < 2 * mt_half ? FMAX * 2 + (mt - mt_half) * 32 : -1);
        }
        for (int i = 0; i < 16; i++) {
            mbar_wait(bar_full + 8 * st, ph);
#pragma unroll
            for (int ks = 0; ks < 2; ks++) {
                const int k0 = i * 32 + ks * 16;
                const uint32_t b0 = g < 2 ? xb[g * 256 + k0 / 2 + t] : 0u, b1 = g < 2 ? xb[g * 256 + k0 / 2 + 4 + t] : 0u;
                const uint32_t rowa = sb + st * FSTAGE_BYTES + (ks * 16 + r + 8 * (mi >> 1)) * GU_PITCH + (mi & 1) * 16;
#pragma unroll
                for (int k = 0; k < 6; k++) {
                    if (cb[k] >= 0) { uint32_t a[4]; ldsm4t(a, rowa + cb[k]); mma16816(acc[k], a, b0, b1); }
                }
            }
            __syncwarp();
            if (lane == 0) mbar_arrive(bar_empty + 8 * st);
            if (++st == FSTAGES) { st = 0; ph ^= 1; }
        }
        if (t == 0) {
#pragma unroll
            for (int k = 0; k < 6; k++) {
                if (cb[k] >= 0) {
                    const int c = cb[k] / 2 + g;
                    pre[c] = acc[k][0]; pre[2 * FMAX + c] = acc[k][1];
                    pre[c + 8] = acc[k][2]; pre[2 * FMAX + c + 8] = acc[k][3];
                }
            }
        }
        named_sync(1, (NCW + NEW) * 32);
#pragma unroll 1
        for (int i = tid; i < nf; i += (NCW + NEW) * 32) {
            const int b = i / (nf / 2), c = 2 * (i % (nf / 2));
            float h[2];
#pragma unroll
            for (int e = 0; e < 2; e++) {
                const float gt = bf16r(pre[b * 2 * FMAX + c + e]), up = bf16r(pre[b * 2 * FMAX + FMAX + c + e]);
                const float ge = bf16r(0.5f * gt * (1.f + tanhf(0.7978845608028654f * (gt + 0.044715f * gt * gt * gt))));
                h[e] = ge * up;
            }
            hb[b * (FMAX / 2) + c / 2] = pack_bf16(h[0], h[1]);
        }
        named_sync(1, (NCW + NEW) * 32);
#pragma unroll
        for (int k = 0; k < 4; k++) { acc[k][0] = acc[k][1] = acc[k][2] = acc[k][3] = 0.f; }
        for (int i = 0; i < ndn; i++) {
            mbar_wait(bar_full + 8 * st, ph);
#pragma unroll
            for (int ks = 0; ks < 2; ks++) {
                const int k0 = i * 32 + ks * 16;
                const uint32_t b0 = g < 2 ? hb[g * (FMAX / 2) + k0 / 2 + t] : 0u, b1 = g < 2 ? hb[g * (FMAX / 2) + k0 / 2 + 4 + t] : 0u;
                const uint32_t rowa = sb + st * FSTAGE_BYTES + (ks * 16 + r + 8 * (mi >> 1)) * DN_PITCH + (mi & 1) * 16 + warp * 128;
#pragma unroll
                for (int k = 0; k < 4; k++) { uint32_t a[4]; ldsm4t(a, rowa + k * 32); mma16816(acc[k], a, b0, b1); }
            }
            __syncwarp();
            if (lane == 0) mbar_arrive(bar_empty + 8 * st);
            if (++st == FSTAGES) { st = 0; ph ^= 1; }
        }
        if (t == 0) {
#pragma unroll
            for (int k = 0; k < 4; k++) {
                const int c = warp * 64 + k * 16 + g;
                st_ll2(&g_ffn[fc][0][c], __float_as_uint(acc[k][0]), tag);
                st_ll2(&g_ffn[fc][1][c], __float_as_uint(acc[k][1]), tag);
                st_ll2(&g_ffn[fc][0][c + 8], __float_as_uint(acc[k][2]), tag);
                st_ll2(&g_ffn[fc][1][c + 8], __float_as_uint(acc[k][3]), tag);
            }
        }
        named_sync(1, (NCW + NEW) * 32);
        if (tid == 0) { g_epoch[cta * 8] = tag; PROF(7); PROF_FLUSH(0x81); }
    }
}

}

extern "C" void kernel_launch(void* const* d_in, const int* in_sizes, int n_in, void* d_out, int out_size) {
    (void)in_sizes; (void)n_in; (void)out_size;
    static bool configured = false;
    if (!configured) {
        cudaFuncSetAttribute(fused_decode_kernel, cudaFuncAttributeMaxDynamicSharedMemorySize, SM_TOTAL);
        configured = true;
    }
    fused_decode_kernel<<<NCTA, NTHREADS, SM_TOTAL>>>(
        (const __nv_bfloat16*)d_in[0], (const __nv_bfloat16*)d_in[1], (const __nv_bfloat16*)d_in[2],
        (const __nv_bfloat16*)d_in[3], (const __nv_bfloat16*)d_in[4], (const __nv_bfloat16*)d_in[6],
        (const __nv_bfloat16*)d_in[7], (const __nv_bfloat16*)d_in[8], (__nv_bfloat16*)d_out);
}
```

```cpp
#include <cuda_runtime.h>
#include <cuda_bf16.h>
#include <stdint.h>

namespace {

constexpr int DM = 512;
constexpr int NH = 32;
constexpr int SK = 8192;
constexpr int DH = 128;
constexpr int FF = 1376;

constexpr int NATT = 128;
constexpr int NFFN = 4;
constexpr int NCTA = NATT + NFFN;
constexpr int G = 16;
constexpr int PH = G / 2;
constexpr int TK = 64;
constexpr int TILE_BYTES = TK * DH * 2;
constexpr int TPP = SK / TK / G;
constexpr int NSLOT = 12;
#define KDEPTH 3
constexpr int DEPTH = KDEPTH;
constexpr int NLOAD = 2 * PH * TPP;
constexpr int DS = DH / G;
constexpr int SPL = 32 / G;
constexpr int PSTRIDE = DH / 4 + 2;

#define KWFIRST 5
constexpr int WFIRST = KWFIRST;
constexpr int WROWS = (PH - 1 - WFIRST) * DS;
constexpr int WSLOT_ROWS = TILE_BYTES / (DM * 2);
constexpr int WSLOTS = (WROWS + WSLOT_ROWS - 1) / WSLOT_ROWS;

constexpr int NCW = 4;
constexpr int NEW = 4;
constexpr int NTHREADS = (NCW + NEW + 1) * 32;

constexpr int FMAX = 352;
constexpr int GU_PITCH = 2 * FMAX * 2 + 16;
constexpr int DN_PITCH = DM * 2 + 16;
constexpr int FSTAGE_BYTES = 32 * GU_PITCH;
constexpr int FSTAGES = 4;

constexpr int SM_P = NSLOT * TILE_BYTES;
constexpr int P_T = 136;
constexpr int P_W = 4 * P_T + 8;
constexpr int SM_ML = SM_P + 2 * NCW * P_W * 4;
constexpr int SM_QS = SM_ML + 2 * NCW * 2 * 4;
constexpr int SM_XN = SM_QS + PH * 64 * 4;
constexpr int SM_RED = SM_XN + 2 * DM * 4;
constexpr int SM_BAR = SM_RED + 8 * 64 * 4;
constexpr int SM_TOTAL = SM_BAR + 64 * 8;
static_assert(FSTAGES * FSTAGE_BYTES <= NSLOT * TILE_BYTES, "ffn ring");
static_assert(2 * 2 * FMAX * 4 + 2 * FMAX * 2 <= 2 * NCW * P_W * 4, "ffn scratch");
static_assert(SM_TOTAL <= 232448, "smem");
static_assert(NCW == 4 && NEW == 4 && DS == 4 * SPL, "barrier counts / lane maps");

#define PACE_TAU 670
#define PACE_OFF 1400
#define LAG1 900
#define FFN_TAU 0
#define WPACE_TAU 340
#define WDEPTH 3
constexpr float LOG2E = 1.4426950408889634f;
constexpr int SPIN_LIMIT = 1 << 22;

__device__ uint2 g_q[2][NH * DH / 2];
__device__ uint4 g_part[2 * NH][G][PSTRIDE];
__device__ uint4 g_fin[2][DM / 8][NATT / 2][2];
__device__ uint2 g_ffn[NFFN][2][DM];
__device__ unsigned int g_epoch[NCTA * 8];

__device__ __forceinline__ unsigned long long gtime() {
    unsigned long long t; asm volatile("mov.u64 %0, %globaltimer;" : "=l"(t)); return t;
}
#define PROF(i) do {} while (0)
#define PROF_FLUSH(mask) do {} while (0)
#define PROFV(i, v) do {} while (0)

__device__ __forceinline__ float bf16r(float x) { return __bfloat162float(__float2bfloat16_rn(x)); }
__device__ __forceinline__ float bf_lo(uint32_t u) { return __uint_as_float(u << 16); }
__device__ __forceinline__ float bf_hi(uint32_t u) { return __uint_as_float(u & 0xffff0000u); }
__device__ __forceinline__ uint32_t pack_bf16(float lo, float hi) {
    uint32_t r; asm("cvt.rn.bf16x2.f32 %0, %1, %2;" : "=r"(r) : "f"(hi), "f"(lo)); return r;
}
__device__ __forceinline__ float ex2(float x) { float r; asm("ex2.approx.ftz.f32 %0, %1;" : "=f"(r) : "f"(x)); return r; }

__device__ __forceinline__ void mbar_init(uint32_t a, uint32_t c) {
    asm volatile("mbarrier.init.shared::cta.b64 [%0], %1;" ::"r"(a), "r"(c) : "memory");
}
__device__ __forceinline__ void mbar_expect_tx(uint32_t a, uint32_t b) {
    asm volatile("mbarrier.arrive.expect_tx.shared::cta.b64 _, [%0], %1;" ::"r"(a), "r"(b) : "memory");
}
__device__ __forceinline__ void mbar_arrive(uint32_t a) {
    asm volatile("mbarrier.arrive.shared::cta.b64 _, [%0];" ::"r"(a) : "memory");
}
__device__ __forceinline__ void mbar_wait(uint32_t a, uint32_t ph) {
    uint32_t ok; int it = 0;
    do {
        asm volatile("{.reg .pred p; mbarrier.try_wait.parity.shared::cta.b64 p, [%1], %2; selp.u32 %0,1,0,p;}"
                     : "=r"(ok) : "r"(a), "r"(ph) : "memory");
        if (++it > SPIN_LIMIT) __trap();
    } while (!ok);
}
__device__ __forceinline__ bool mbar_test(uint32_t a, uint32_t ph) {
    uint32_t ok;
    asm volatile("{.reg .pred p; mbarrier.test_wait.parity.shared::cta.b64 p, [%1], %2; selp.u32 %0,1,0,p;}"
                 : "=r"(ok) : "r"(a), "r"(ph) : "memory");
    return ok;
}
__device__ __forceinline__ void bulk_load(uint32_t dst, const void* src, uint32_t bytes, uint32_t bar, uint64_t pol) {
    asm volatile("cp.async.bulk.shared::cluster.global.mbarrier::complete_tx::bytes.L2::cache_hint [%0], [%1], %2, [%3], %4;"
                 ::"r"(dst), "l"(src), "r"(bytes), "r"(bar), "l"(pol) : "memory");
}
__device__ __forceinline__ void bulk_load_nohint(uint32_t dst, const void* src, uint32_t bytes, uint32_t bar) {
    asm volatile("cp.async.bulk.shared::cluster.global.mbarrier::complete_tx::bytes [%0], [%1], %2, [%3];"
                 ::"r"(dst), "l"(src), "r"(bytes), "r"(bar) : "memory");
}
__device__ __forceinline__ void named_sync(int id, int n) { asm volatile("bar.sync %0, %1;" ::"r"(id), "r"(n) : "memory"); }

__device__ __forceinline__ void ldsm4(uint32_t (&r)[4], uint32_t a) {
    asm volatile("ldmatrix.sync.aligned.m8n8.x4.shared.b16 {%0,%1,%2,%3}, [%4];"
                 : "=r"(r[0]), "=r"(r[1]), "=r"(r[2]), "=r"(r[3]) : "r"(a) : "memory");
}
__device__ __forceinline__ void ldsm4t(uint32_t (&r)[4], uint32_t a) {
    asm volatile("ldmatrix.sync.aligned.m8n8.x4.trans.shared.b16 {%0,%1,%2,%3}, [%4];"
                 : "=r"(r[0]), "=r"(r[1]), "=r"(r[2]), "=r"(r[3]) : "r"(a) : "memory");
}
__device__ __forceinline__ void mma16816(float (&c)[4], const uint32_t (&a)[4], uint32_t b0, uint32_t b1) {
    asm volatile("mma.sync.aligned.m16n8k16.row.col.f32.bf16.bf16.f32 {%0,%1,%2,%3}, {%4,%5,%6,%7}, {%8,%9}, {%0,%1,%2,%3};"
                 : "+f"(c[0]), "+f"(c[1]), "+f"(c[2]), "+f"(c[3])
                 : "r"(a[0]), "r"(a[1]), "r"(a[2]), "r"(a[3]), "r"(b0), "r"(b1));
}

__device__ __forceinline__ uint4 ld_ll(const void* p) {
    uint4 v;
    asm volatile("ld.relaxed.gpu.global.v4.u32 {%0,%1,%2,%3}, [%4];"
                 : "=r"(v.x), "=r"(v.y), "=r"(v.z), "=r"(v.w) : "l"(p) : "memory");
    return v;
}
__device__ __forceinline__ void st_ll2(void* p, uint32_t a, uint32_t tag) {
    asm volatile("st.relaxed.gpu.global.v2.u32 [%0], {%1,%2};" ::"l"(p), "r"(a), "r"(tag) : "memory");
}
__device__ __forceinline__ void st_ll16(void* p, uint32_t a, uint32_t b, uint32_t c, uint32_t tag) {
    asm volatile("{.reg .b128 t; .reg .b64 lo, hi; mov.b64 lo, {%1,%2}; mov.b64 hi, {%3,%4}; mov.b128 t, {lo, hi};\n\t"
                 "st.relaxed.gpu.global.b128 [%0], t;}" ::"l"(p), "r"(a), "r"(b), "r"(c), "r"(tag) : "memory");
}
__device__ __forceinline__ void ld_ll16_missing(uint4& v, const void* p, uint32_t tag) {
    asm volatile("{.reg .pred q; setp.ne.u32 q, %3, %5;\n\t"
                 "@q ld.relaxed.gpu.global.v4.u32 {%0,%1,%2,%3}, [%4];}"
                 : "+r"(v.x), "+r"(v.y), "+r"(v.z), "+r"(v.w) : "l"(p), "r"(tag) : "memory");
}
__device__ __forceinline__ void st_pack4(void* p, float a, float b, float c, float d, uint32_t tag) {
    const uint32_t ua = __float_as_uint(a) + 0x80u, ub = __float_as_uint(b) + 0x80u;
    const uint32_t uc = __float_as_uint(c) + 0x80u, ud = __float_as_uint(d) + 0x80u;
    st_ll16(p, __byte_perm(ua, ub, 0x5321), __byte_perm(ub, uc, 0x6532), __byte_perm(uc, ud, 0x7653), tag);
}
__device__ __forceinline__ void unpack4(const uint4& u, float (&v)[4]) {
    v[0] = __uint_as_float(u.x << 8);
    v[1] = __uint_as_float(__byte_perm(u.x, u.y, 0x5430) & 0xffffff00u);
    v[2] = __uint_as_float(__byte_perm(u.y, u.z, 0x4320) & 0xffffff00u);
    v[3] = __uint_as_float(u.z & 0xffffff00u);
}
__device__ __forceinline__ void st_u16_if(void* p, uint32_t v, bool on) {
    asm volatile("{.reg .pred q; setp.ne.u32 q, %2, 0; @q st.global.u16 [%0], %1;}" ::"l"(p), "h"((unsigned short)v), "r"((uint32_t)on) : "memory");
}
__device__ __forceinline__ void st_u32_if(void* p, uint32_t v, bool on) {
    asm volatile("{.reg .pred q; setp.ne.u32 q, %2, 0; @q st.global.u32 [%0], %1;}" ::"l"(p), "r"(v), "r"((uint32_t)on) : "memory");
}
__device__ __forceinline__ bool ll_ok(const uint4& v, uint32_t tag) { return v.y == tag && v.w == tag; }

__device__ __forceinline__ float warp_max(float v) {
    int i = __float_as_int(v);
    i = i >= 0 ? i : (i ^ 0x7fffffff);
    i = __reduce_max_sync(0xffffffffu, i);
    i = i >= 0 ? i : (i ^ 0x7fffffff);
    return __int_as_float(i);
}

__device__ __forceinline__ float rcp_approx(float x) { float r; asm("rcp.approx.ftz.f32 %0, %1;" : "=f"(r) : "f"(x)); return r; }

__device__ __noinline__ void layernorm_row(uint4 u0, uint4 u1, uint32_t* dst, int lane) {
    uint32_t w[8] = {u0.x, u0.y, u0.z, u0.w, u1.x, u1.y, u1.z, u1.w};
    float y[16];
    float s = 0.f;
#pragma unroll
    for (int i = 0; i < 8; i++) { y[2 * i] = bf_lo(w[i]); y[2 * i + 1] = bf_hi(w[i]); s += y[2 * i] + y[2 * i + 1]; }
#pragma unroll
    for (int o = 16; o > 0; o >>= 1) s += __shfl_xor_sync(0xffffffffu, s, o);
    const float mean = s * (1.f / DM);
    float v = 0.f;
#pragma unroll
    for (int i = 0; i < 16; i++) { const float d = y[i] - mean; v = fmaf(d, d, v); }
#pragma unroll
    for (int o = 16; o > 0; o >>= 1) v += __shfl_xor_sync(0xffffffffu, v, o);
    const float mb = bf16r(mean);
    float sd;
    asm("sqrt.approx.f32 %0, %1;" : "=f"(sd) : "f"(bf16r(bf16r(v * (1.f / DM)) + 1e-5f)));
    const float inv = rcp_approx(bf16r(sd));
#pragma unroll
    for (int i = 0; i < 8; i++) {
        const uint32_t d = pack_bf16(y[2 * i] - mb, y[2 * i + 1] - mb);
        w[i] = pack_bf16(bf_lo(d) * inv, bf_hi(d) * inv);
    }
    *(uint4*)(dst + 4 * lane) = make_uint4(w[0], w[1], w[2], w[3]);
    *(uint4*)(dst + 128 + 4 * lane) = make_uint4(w[4], w[5], w[6], w[7]);
}

__device__ __noinline__ float4 wo_project(float4 acc, uint32_t w, uint32_t o, int rows) {
#pragma unroll 1
    for (int r = 0; r < rows; r += 4) {
        float4 ov;
        uint32_t a[4], b[4];
        asm volatile("ld.shared.v4.f32 {%0,%1,%2,%3}, [%4];" : "=f"(ov.x), "=f"(ov.y), "=f"(ov.z), "=f"(ov.w) : "r"(o + 4 * r));
#pragma unroll
        for (int i = 0; i < 4; i++)
            asm volatile("ld.shared.v2.u32 {%0,%1}, [%2];" : "=r"(a[i]), "=r"(b[i]) : "r"(w + (r + i) * (DM * 2)));
        const float of[4] = {ov.x, ov.y, ov.z, ov.w};
#pragma unroll
        for (int i = 0; i < 4; i++) {
            acc.x = fmaf(of[i], bf_lo(a[i]), acc.x); acc.y = fmaf(of[i], bf_hi(a[i]), acc.y);
            acc.z = fmaf(of[i], bf_lo(b[i]), acc.z); acc.w = fmaf(of[i], bf_hi(b[i]), acc.w);
        }
    }
    return acc;
}

__device__ __noinline__ void ffn_cta(const __nv_bfloat16* __restrict__ x, const __nv_bfloat16* __restrict__ wg,
                                     const __nv_bfloat16* __restrict__ wu, const __nv_bfloat16* __restrict__ wd);
__device__ __noinline__ void attn_workers(const __nv_bfloat16* __restrict__ x, const __nv_bfloat16* __restrict__ wq,
                                          const __nv_bfloat16* __restrict__ wo, __nv_bfloat16* __restrict__ out);

__global__ void __launch_bounds__(NTHREADS, 1)
fused_decode_kernel(const __nv_bfloat16* __restrict__ x, const __nv_bfloat16* __restrict__ kc,
                    const __nv_bfloat16* __restrict__ vc, const __nv_bfloat16* __restrict__ wq,
                    const __nv_bfloat16* __restrict__ wo, const __nv_bfloat16* __restrict__ wg,
                    const __nv_bfloat16* __restrict__ wu, const __nv_bfloat16* __restrict__ wd,
                    __nv_bfloat16* __restrict__ out) {
    extern __shared__ __align__(1024) unsigned char smem[];
    const uint32_t sb = (uint32_t)__cvta_generic_to_shared(smem);
    const int cta = blockIdx.x;
    const uint32_t bar_full = sb + SM_BAR, bar_empty = bar_full + 8 * NSLOT;
    const uint32_t bar_q = bar_empty + 8 * NSLOT + 32;
    volatile int* progress = (volatile int*)(smem + SM_BAR + 60 * 8);
    const int grp = cta / G, rk = cta % G;

    if (__builtin_expect(threadIdx.x < 32 && cta < NATT, 1)) {
        uint64_t pol = 0;
        const size_t base = ((size_t)grp * PH * SK + (size_t)rk * TK) * DH * 2;
        const char* src0 = (const char*)kc + base;
        const char* src1 = (const char*)vc + base;
        uint32_t t0 = 0;
        if (threadIdx.x == 0) {
            t0 = (uint32_t)gtime();
            PROF(0);
            mbar_init(bar_full, 1);
            asm volatile("fence.mbarrier_init.release.cluster;" ::: "memory");
            asm volatile("fence.proxy.async.shared::cta;" ::: "memory");
            asm volatile("createpolicy.fractional.L2::evict_first.b64 %0, 1.0;" : "=l"(pol));
            mbar_expect_tx(bar_full, TILE_BYTES);
            bulk_load(sb, src0, TILE_BYTES, bar_full, pol);
            { const char* nx = src0 + G * TILE_BYTES; src0 = src1; src1 = nx; }
            PROF(11);
#pragma unroll 1
            for (int i = 1; i < NSLOT; i++) mbar_init(bar_full + 8 * i, 1);
#pragma unroll 1
            for (int i = 0; i < NSLOT + 4; i++) mbar_init(bar_empty + 8 * i, 4);
            mbar_init(bar_q, 1); mbar_init(bar_q + 8, NEW); mbar_init(bar_q + 16, 1); mbar_init(bar_q + 24, NCW);
            *progress = 0;
            asm volatile("fence.mbarrier_init.release.cluster;" ::: "memory");
            asm volatile("fence.proxy.async.shared::cta;" ::: "memory");
        }
        __syncwarp();
        asm volatile("bar.arrive 0, %0;" ::"n"(NTHREADS) : "memory");
        if (threadIdx.x == 0) {
            int st = 1, ph = 1;
            int ws = 0, wph = 0;
            int landed = 0;
#pragma unroll 1
            for (int i = 1; i < NLOAD; i++) {
                for (int it = 0;; it++) {
                    const int lag = (int)((uint32_t)gtime() - t0) - (i * PACE_TAU + PACE_OFF);
                    if (lag >= 0 && i - landed < DEPTH + (lag > LAG1)) break;
                    if (landed < i && mbar_test(bar_full + 8 * ws, wph)) {
                        if (landed == 0) PROF(12);
                        ++landed;
                        if (++ws == NSLOT) { ws = 0; wph ^= 1; }
                    }
                    if (it > SPIN_LIMIT) __trap();
                }
                mbar_wait(bar_empty + 8 * st, ph);
                mbar_expect_tx(bar_full + 8 * st, TILE_BYTES);
                bulk_load(sb + st * TILE_BYTES, src0, TILE_BYTES, bar_full + 8 * st, pol);
                const char* nx = src0 + G * TILE_BYTES; src0 = src1; src1 = nx;
                if (++st == NSLOT) { st = 0; ph ^= 1; }
            }
            PROF(1);
            const char* wsrc = (const char*)(wo + (size_t)(((grp % (NH / PH)) * PH + WFIRST) * DH + rk * DS) * DM);
#pragma unroll 1
            for (int i = 0; i < WSLOTS; i++) {
                while (NLOAD + i - landed >= WDEPTH) {
                    mbar_wait(bar_full + 8 * ws, wph);
                    ++landed;
                    if (++ws == NSLOT) { ws = 0; wph ^= 1; }
                }
                while ((uint32_t)gtime() - t0 < (uint32_t)(NLOAD * PACE_TAU + PACE_OFF + i * WPACE_TAU)) {}
                mbar_wait(bar_empty + 8 * st, ph);
                const int np = min(WSLOT_ROWS, WROWS - i * WSLOT_ROWS) / DS;
                mbar_expect_tx(bar_full + 8 * st, np * DS * DM * 2);
#pragma unroll 1
                for (int k = 0; k < np; k++) {
                    bulk_load_nohint(sb + st * TILE_BYTES + k * (DS * DM * 2), wsrc, DS * DM * 2, bar_full + 8 * st);
                    wsrc += DH * DM * 2;
                }
                if (++st == NSLOT) { st = 0; ph ^= 1; }
            }
            PROF_FLUSH(0x1803);
        }
        return;
    }
    if (cta >= NATT) ffn_cta(x, wg, wu, wd);
    else attn_workers(x, wq, wo, out);
}

__device__ __noinline__ void attn_workers(const __nv_bfloat16* __restrict__ x, const __nv_bfloat16* __restrict__ wq,
                                          const __nv_bfloat16* __restrict__ wo, __nv_bfloat16* __restrict__ out) {
    extern __shared__ __align__(1024) unsigned char smem[];
    const uint32_t sb = (uint32_t)__cvta_generic_to_shared(smem);
    const int cta = blockIdx.x;
    const uint32_t bar_full = sb + SM_BAR, bar_empty = bar_full + 8 * NSLOT;
    const uint32_t bar_pfull = bar_empty + 8 * NSLOT, bar_pempty = bar_pfull + 16, bar_q = bar_pempty + 16;
    volatile int* progress = (volatile int*)(smem + SM_BAR + 60 * 8);
    const int grp = cta / G, rk = cta % G;
    {
        const int tid = threadIdx.x - 32, warp = tid >> 5, lane = tid & 31;
        const int g = lane >> 2, t = lane & 3;
        uint32_t* xb = (uint32_t*)(smem + SM_XN);
        float* red = (float*)(smem + SM_RED);
        uint4 wv[8];
        uint4 u0 = make_uint4(0, 0, 0, 0), u1 = u0;
        if (warp < 2) { u0 = __ldg((const uint4*)(x + warp * DM) + lane); u1 = __ldg((const uint4*)(x + warp * DM + 256) + lane); }
        {
            const uint4* src = (const uint4*)(wq + (size_t)(tid >> 2) * (NH * DH) + cta * 32 + (tid & 3) * 8);
#pragma unroll
            for (int i = 0; i < 8; i++) wv[i] = __ldg(src + (size_t)i * 64 * (NH * DH / 8));
        }
        if (warp == NCW) st_ll2(&g_q[lane >> 4][cta * 16 + (lane & 15)], 0u, 0u);
        uint32_t tag;
        asm volatile("ld.relaxed.gpu.global.u32 %0, [%1];" : "=r"(tag) : "l"(&g_epoch[cta * 8]) : "memory");
        if (warp < 2) layernorm_row(u0, u1, xb + warp * 256, lane);
        named_sync(0, NTHREADS);
        tag += 1;
        if (tid == 0) PROF(8);
        {
            float a0[8], a1[8];
#pragma unroll
            for (int c = 0; c < 8; c++) { a0[c] = 0.f; a1[c] = 0.f; }
#pragma unroll
            for (int i = 0; i < 8; i++) {
                const float x0 = __bfloat162float(((const __nv_bfloat16*)xb)[(tid >> 2) + 64 * i]);
                const float x1 = __bfloat162float(((const __nv_bfloat16*)xb)[DM + (tid >> 2) + 64 * i]);
                const uint32_t w[4] = {wv[i].x, wv[i].y, wv[i].z, wv[i].w};
#pragma unroll
                for (int c = 0; c < 4; c++) {
                    const float lo = bf_lo(w[c]), hi = bf_hi(w[c]);
                    a0[2 * c] = fmaf(x0, lo, a0[2 * c]); a0[2 * c + 1] = fmaf(x0, hi, a0[2 * c + 1]);
                    a1[2 * c] = fmaf(x1, lo, a1[2 * c]); a1[2 * c + 1] = fmaf(x1, hi, a1[2 * c + 1]);
                }
            }
            const bool b4 = lane & 16, b3 = lane & 8, b2 = lane & 4;
            float r8[8], r4[4], r2[2];
#pragma unroll
            for (int c = 0; c < 8; c++) {
                const float keep = b4 ? a1[c] : a0[c], send = b4 ? a0[c] : a1[c];
                r8[c] = keep + __shfl_xor_sync(0xffffffffu, send, 16);
            }
#pragma unroll
            for (int c = 0; c < 4; c++) {
                const float keep = b3 ? r8[4 + c] : r8[c], send = b3 ? r8[c] : r8[4 + c];
                r4[c] = keep + __shfl_xor_sync(0xffffffffu, send, 8);
            }
#pragma unroll
            for (int c = 0; c < 2; c++) {
                const float keep = b2 ? r4[2 + c] : r4[c], send = b2 ? r4[c] : r4[2 + c];
                r2[c] = keep + __shfl_xor_sync(0xffffffffu, send, 4);
            }
            const int col = (b4 ? 32 : 0) + t * 8 + (b3 ? 4 : 0) + (b2 ? 2 : 0);
            *(float2*)&red[warp * 64 + col] = make_float2(r2[0], r2[1]);
        }
        named_sync(1, (NCW + NEW) * 32);

        if (warp < NCW) {
            const int r = lane & 7, mi = lane >> 3;
            uint32_t koff[4], voff[4];
#pragma unroll
            for (int j = 0; j < 4; j++) {
                koff[j] = sb + (warp * 16 + r + 8 * (mi & 1)) * 256 + (((2 * j + (mi >> 1)) ^ r) << 4);
                voff[j] = sb + (warp * 16 + r + 8 * (mi >> 1)) * 256 + (((2 * j + (mi & 1)) ^ r) << 4);
            }
            const bool owner = (t == (g >> 1));
            const bool odd = g & 1;
            const uint32_t* qs = (const uint32_t*)(smem + SM_QS);
            float* P = (float*)(smem + SM_P);
            float* ml = (float*)(smem + SM_ML);
            int st = 0, ph = 0;
            wo_project(make_float4(0.f, 0.f, 0.f, 0.f), sb + 8 * tid, sb + SM_XN, 4);
            mbar_wait(bar_q, 0);
            if (tid == 0) PROF(2);
            for (int j = 0; j < PH; j++) {
                if (j == 1) mbar_wait(bar_q + 8, 0);
                uint32_t qb[8][2];
#pragma unroll
                for (int k = 0; k < 8; k++) {
                    qb[k][0] = qs[j * 64 + (((2 * k) ^ g) << 2) + t];
                    qb[k][1] = qs[j * 64 + (((2 * k + 1) ^ g) << 2) + t];
                }
                float acc[8][4];
#pragma unroll
                for (int k = 0; k < 8; k++) { acc[k][0] = acc[k][1] = acc[k][2] = acc[k][3] = 0.f; }
                float m = -INFINITY, l = 0.f;
#pragma unroll 1
                for (int tt = 0; tt < TPP; tt++) {
                    uint32_t a[8][4];
                    mbar_wait(bar_full + 8 * st, ph);
                    {
                        const uint32_t so = st * TILE_BYTES;
#pragma unroll
                        for (int k = 0; k < 8; k++) ldsm4(a[k], koff[k & 3] + so + (k >> 2) * 128);
                    }
                    float c0[4] = {0.f, 0.f, 0.f, 0.f}, c1[4] = {0.f, 0.f, 0.f, 0.f};
#pragma unroll
                    for (int k = 0; k < 8; k += 2) {
                        mma16816(c0, a[k], qb[k][0], qb[k][1]);
                        mma16816(c1, a[k + 1], qb[k + 1][0], qb[k + 1][1]);
                    }
                    __syncwarp();
                    if (lane == 0) mbar_arrive(bar_empty + 8 * st);
                    ++st;
                    float s0 = odd ? (c0[1] + c1[1]) : (c0[0] + c1[0]);
                    float s1 = odd ? (c0[3] + c1[3]) : (c0[2] + c1[2]);
                    s0 = bf16r(bf16r(s0) * 0.08838834764831845f);
                    s1 = bf16r(bf16r(s1) * 0.08838834764831845f);
                    if (!owner) { s0 = -INFINITY; s1 = -INFINITY; }
                    const float mx = fmaxf(s0, s1);
                    if (__any_sync(0xffffffffu, mx > m)) {
                        const float mn = warp_max(mx);
                        const float alpha = ex2((m - mn) * LOG2E);
                        m = mn;
                        l *= alpha;
#pragma unroll
                        for (int k = 0; k < 8; k++) { acc[k][0] *= alpha; acc[k][1] *= alpha; acc[k][2] *= alpha; acc[k][3] *= alpha; }
                    }
                    const float p0 = ex2((s0 - m) * LOG2E), p1 = ex2((s1 - m) * LOG2E);
                    l += p0 + p1;
                    const uint32_t b0 = odd ? pack_bf16(0.f, p0) : pack_bf16(p0, 0.f);
                    const uint32_t b1 = odd ? pack_bf16(0.f, p1) : pack_bf16(p1, 0.f);
                    if (tt == TPP - 1) {
#pragma unroll
                        for (int o = 16; o > 0; o >>= 1) l += __shfl_xor_sync(0xffffffffu, l, o);
                        if (j >= 2) mbar_wait(bar_pempty + 8 * (j & 1), ((j >> 1) - 1) & 1);
                        if (lane == 0) { ml[((j & 1) * NCW + warp) * 2] = m; ml[((j & 1) * NCW + warp) * 2 + 1] = l; }
                    }
                    mbar_wait(bar_full + 8 * st, ph);
                    {
                        const uint32_t so = st * TILE_BYTES;
#pragma unroll
                        for (int k = 0; k < 8; k++) ldsm4t(a[k], voff[k & 3] + so + (k >> 2) * 128);
                    }
#pragma unroll
                    for (int k = 0; k < 8; k++) mma16816(acc[k], a[k], b0, b1);
                    __syncwarp();
                    if (lane == 0) mbar_arrive(bar_empty + 8 * st);
                    if (++st == NSLOT) { st = 0; ph ^= 1; }
                    if (tt == 1 && tid == 0) *progress = j;
                }
                float* Pw = P + ((j & 1) * NCW + warp) * P_W + t * P_T + g;
#pragma unroll
                for (int k = 0; k < 8; k++) {
                    Pw[((k ^ t) * 2) * 8] = acc[k][0] + acc[k][3];
                    Pw[((k ^ t) * 2 + 1) * 8] = acc[k][2] + acc[k][1];
                }
                __syncwarp();
                if (lane == 0) mbar_arrive(bar_pfull + 8 * (j & 1));
            }
            if (tid == 0) PROF(3);
            float4 sp = make_float4(0.f, 0.f, 0.f, 0.f);
            mbar_wait(bar_q + 16, 0);
#pragma unroll 1
            for (int i = 0; i < WSLOTS; i++) {
                mbar_wait(bar_full + 8 * st, ph);
                sp = wo_project(sp, sb + st * TILE_BYTES + 8 * tid, sb + SM_XN + i * WSLOT_ROWS * 4,
                                min(WSLOT_ROWS, WROWS - i * WSLOT_ROWS));
                if (++st == NSLOT) { st = 0; ph ^= 1; }
            }
            *(float4*)&red[4 * tid] = sp;
            __syncwarp();
            if (lane == 0) mbar_arrive(bar_q + 24);
            if (tid == 0) { PROF(9); PROF_FLUSH(0x30c); }
            return;
        }

        const int et = tid - NCW * 32;
        if (warp == NCW) {
            float2 s = make_float2(0.f, 0.f);
#pragma unroll
            for (int w = 0; w < NCW + NEW; w++) { const float2 v = *(const float2*)&red[w * 64 + 2 * lane]; s.x += v.x; s.y += v.y; }
            st_ll2(&g_q[lane >> 4][cta * 16 + (lane & 15)], pack_bf16(s.x, s.y), tag);
            if (lane == 0) PROF(10);
        }
        const int bb = grp / (NH / PH);
        const int h0 = (grp % (NH / PH)) * PH;
        {
            uint32_t* qs = (uint32_t*)(smem + SM_QS);
            const uint2* src = &g_q[bb][h0 * 64];
            if (warp == NCW + 1) {
                uint4 v; int it = 0;
                do { v = ld_ll(src + 2 * lane); if (++it > SPIN_LIMIT) __trap(); } while (!ll_ok(v, tag));
                *(uint2*)&qs[2 * lane] = make_uint2(v.x, v.z);
                __syncwarp();
                if (lane == 0) mbar_arrive(bar_q);
            }
            mbar_wait(bar_q, 0);
            __nanosleep(2000);
            for (int i = 32 + et; i < PH * 32; i += NEW * 32) {
                uint4 v; int it = 0;
                while (true) {
                    v = ld_ll(src + 2 * i);
                    if (ll_ok(v, tag)) break;
                    if (++it > SPIN_LIMIT) __trap();
                    __nanosleep(500);
                }
                *(uint2*)&qs[2 * i] = make_uint2(v.x, v.z);
            }
            __syncwarp();
            if (lane == 0) mbar_arrive(bar_q + 8);
        }
        const float* P = (const float*)(smem + SM_P);
        const float* ml = (const float*)(smem + SM_ML);
        float sacc[4] = {0.f, 0.f, 0.f, 0.f};
        float gate = 0.f, xres = 0.f;
        const int fb = cta / (NATT / 2), cg = cta % (NATT / 2);
        const int fcol = cg * 8 + (lane & 1) * 4 + (lane & 2) + ((lane >> 2) & 1);
#pragma unroll 1
        for (int j = 0; j < PH; j++) {
            const int head = grp * PH + j;
            const bool last = (j == PH - 1);
            uint2 wr[DS];
#pragma unroll
            for (int i = 0; i < DS; i++) wr[i] = make_uint2(0u, 0u);
            if (last || j < WFIRST) {
                const uint2* src = (const uint2*)(wo + (size_t)((h0 + j) * DH + rk * DS) * DM) + et;
#pragma unroll
                for (int i = 0; i < DS; i++) wr[i] = __ldg(src + i * (DM / 4));
            }
            if (last && warp == NCW) {
                uint2 v; int it = 0;
                while (true) {
                    asm volatile("ld.relaxed.gpu.global.v2.u32 {%0,%1}, [%2];" : "=r"(v.x), "=r"(v.y) : "l"(&g_ffn[lane >> 3][fb][fcol]) : "memory");
                    if (!__any_sync(0xffffffffu, v.y != tag)) break;
                    if (++it > SPIN_LIMIT) __trap();
                    __nanosleep(500);
                }
                float f = __uint_as_float(v.x);
                f += __shfl_xor_sync(0xffffffffu, f, 8);
                f += __shfl_xor_sync(0xffffffffu, f, 16);
                f = bf16r(f);
                gate = bf16r(f * rcp_approx(1.f + ex2(-f * LOG2E)));
                xres = __bfloat162float(x[fb * DM + fcol]);
            }
            uint4* dst_o = &g_part[head][rk][et >> 2];
            uint4* dst_ml = &g_part[head][rk][DH / 4 + (et & 1)];
            const uint4* src_o = &g_part[head][lane / SPL][rk * SPL + lane % SPL];
            const uint4* src_ml = &g_part[head][lane / SPL][DH / 4];
            uint4* dst_fin = &g_fin[bb][et >> 1][cta % (NATT / 2)][et & 1];
            float wf[DS][4];
#pragma unroll
            for (int i = 0; i < DS; i++) {
                wf[i][0] = bf_lo(wr[i].x); wf[i][1] = bf_hi(wr[i].x); wf[i][2] = bf_lo(wr[i].y); wf[i][3] = bf_hi(wr[i].y);
                asm volatile("" : "+f"(wf[i][0]), "+f"(wf[i][1]), "+f"(wf[i][2]), "+f"(wf[i][3]));
            }
            asm volatile("" : "+l"(dst_o), "+l"(dst_ml), "+l"(src_o), "+l"(src_ml), "+l"(dst_fin));
            mbar_wait(bar_pfull + 8 * (j & 1), (j >> 1) & 1);
            if (j == PH - 1 && et == 0) PROF(4);
            {
                const float4 ma = *(const float4*)(ml + (j & 1) * NCW * 2), mb = *(const float4*)(ml + (j & 1) * NCW * 2 + 4);
                const float* Pw = P + ((j & 1) * NCW + t) * P_W + (et >> 2) * 4;
                const float4 p0 = *(const float4*)Pw, p1 = *(const float4*)(Pw + P_T);
                const float4 p2 = *(const float4*)(Pw + 2 * P_T), p3 = *(const float4*)(Pw + 3 * P_T);
                const float M = fmaxf(fmaxf(ma.x, ma.z), fmaxf(mb.x, mb.z));
                const float mw = (t & 2) ? ((t & 1) ? mb.z : mb.x) : ((t & 1) ? ma.z : ma.x);
                const float lw = (t & 2) ? ((t & 1) ? mb.w : mb.y) : ((t & 1) ? ma.w : ma.y);
                const float sc = ex2((mw - M) * LOG2E);
                float o[5] = {sc * ((p0.x + p1.x) + (p2.x + p3.x)), sc * ((p0.y + p1.y) + (p2.y + p3.y)),
                              sc * ((p0.z + p1.z) + (p2.z + p3.z)), sc * ((p0.w + p1.w) + (p2.w + p3.w)), sc * lw};
#pragma unroll
                for (int k = 1; k < 4; k <<= 1) {
#pragma unroll
                    for (int i = 0; i < 5; i++) o[i] += __shfl_xor_sync(0xffffffffu, o[i], k);
                }
                if (t == 0) st_pack4(dst_o, o[0], o[1], o[2], o[3], tag);
                if (et < 2) st_ll16(dst_ml, __float_as_uint(M), __float_as_uint(o[4]), 0u, tag);
                __syncwarp();
                if (lane == 0) mbar_arrive(bar_pempty + 8 * (j & 1));
            }
            if (!last) {
                int it = 0;
                while (*progress <= j) { __nanosleep(250); if (++it > SPIN_LIMIT) __trap(); }
            }
            float v[4], inv;
            {
                uint4 uo = make_uint4(0u, 0u, 0u, 0u), um = uo; int it = 0;
                ld_ll16_missing(uo, src_o, tag); ld_ll16_missing(um, src_ml, tag);
                if (last) {
                    mbar_wait(bar_q + 24, 0);
                    const float4 sp = *(const float4*)&red[4 * et];
                    sacc[0] += sp.x; sacc[1] += sp.y; sacc[2] += sp.z; sacc[3] += sp.w;
                }
                while (__any_sync(0xffffffffu, uo.w != tag || um.w != tag)) {
                    if (++it > SPIN_LIMIT) __trap();
                    if (!last) __nanosleep(500);
                    ld_ll16_missing(uo, src_o, tag); ld_ll16_missing(um, src_ml, tag);
                }
                if (j == PH - 1 && et == 0) PROF(5);
                const float Ms = __uint_as_float(um.x);
                const float Mg = warp_max(Ms);
                const float sc = ex2((Ms - Mg) * LOG2E);
                float L = sc * __uint_as_float(um.y);
                unpack4(uo, v);
#pragma unroll
                for (int i = 0; i < 4; i++) v[i] *= sc;
#pragma unroll
                for (int o = SPL; o < 32; o <<= 1) {
                    L += __shfl_xor_sync(0xffffffffu, L, o);
#pragma unroll
                    for (int i = 0; i < 4; i++) v[i] += __shfl_xor_sync(0xffffffffu, v[i], o);
                }
                inv = rcp_approx(L);
            }
            {
                float y[4] = {0.f, 0.f, 0.f, 0.f};
#pragma unroll
                for (int i = 0; i < DS; i++) {
                    const float o = __shfl_sync(0xffffffffu, v[i & 3], i >> 2);
#pragma unroll
                    for (int c = 0; c < 4; c++) y[c] = fmaf(o, wf[i][c], y[c]);
                }
#pragma unroll
                for (int c = 0; c < 4; c++) sacc[c] = fmaf(y[c], inv, sacc[c]);
            }
            if (last) st_pack4(dst_fin, sacc[0], sacc[1], sacc[2], sacc[3], tag);
            if (!last && j >= WFIRST && warp == NCW) {
                if (lane < SPL) *(float4*)(smem + SM_XN + ((j - WFIRST) * DS + lane * 4) * 4) =
                    make_float4(bf16r(v[0] * inv), bf16r(v[1] * inv), bf16r(v[2] * inv), bf16r(v[3] * inv));
                __syncwarp();
                if (j == PH - 2 && lane == 0) mbar_arrive(bar_q + 16);
            }
            if (j == PH - 2) {
                if (t == 0) st_ll16(dst_o + G * PSTRIDE, 0u, 0u, 0u, 0u);
                if (et < 2) st_ll16(dst_ml + G * PSTRIDE, 0u, 0u, 0u, 0u);
                st_ll16(dst_fin, 0u, 0u, 0u, 0u);
            }
            if (warp == NCW) {
                if (last && lane == 0) PROF(6);
                const uint4* src = &g_fin[fb][cg][0][0] + lane;
                uint4 u[4]; int it = 0;
#pragma unroll
                for (int i = 0; i < 4; i++) u[i] = make_uint4(0u, 0u, 0u, last ? 0u : tag);
                while (true) {
                    if (last && lane == 0) PROF(13);
#pragma unroll
                    for (int i = 0; i < 4; i++) ld_ll16_missing(u[i], src + i * 32, tag);
                    const uint32_t bad = ((u[0].w ^ tag) | (u[1].w ^ tag)) | ((u[2].w ^ tag) | (u[3].w ^ tag));
                    if (!__any_sync(0xffffffffu, bad != 0)) break;
                    if (++it > SPIN_LIMIT) __trap();
                }
                if (last && lane == 0) { PROF(14); PROFV(15, it); }
                float a[4], b[4], c[4], d[4];
                unpack4(u[0], a); unpack4(u[1], b); unpack4(u[2], c); unpack4(u[3], d);
#pragma unroll
                for (int i = 0; i < 4; i++) a[i] = (a[i] + b[i]) + (c[i] + d[i]);
                const bool h1 = lane & 2, h2 = lane & 4;
                const float e0 = (h1 ? a[2] : a[0]) + __shfl_xor_sync(0xffffffffu, h1 ? a[0] : a[2], 2);
                const float e1 = (h1 ? a[3] : a[1]) + __shfl_xor_sync(0xffffffffu, h1 ? a[1] : a[3], 2);
                float sv = (h2 ? e1 : e0) + __shfl_xor_sync(0xffffffffu, h2 ? e0 : e1, 4);
                sv += __shfl_xor_sync(0xffffffffu, sv, 8);
                sv += __shfl_xor_sync(0xffffffffu, sv, 16);
                st_u16_if(out + fb * DM + fcol, pack_bf16(xres + bf16r(bf16r(sv) * gate), 0.f), last && lane < 8);
                st_u32_if(&g_epoch[cta * 8], tag, last && lane == 0);
                if (last && lane == 0) { PROF(7); PROF_FLUSH(0xe4f0); }
            }
        }
        return;
    }

}

__device__ __noinline__ void ffn_cta(const __nv_bfloat16* __restrict__ x, const __nv_bfloat16* __restrict__ wg,
                                     const __nv_bfloat16* __restrict__ wu, const __nv_bfloat16* __restrict__ wd) {
    extern __shared__ __align__(1024) unsigned char smem[];
    const uint32_t sb = (uint32_t)__cvta_generic_to_shared(smem);
    const int tid = threadIdx.x, warp = tid >> 5, lane = tid & 31;
    const int cta = blockIdx.x;
    const int g = lane >> 2, t = lane & 3;
    const uint32_t bar_full = sb + SM_BAR, bar_empty = bar_full + 8 * NSLOT;
    const int fc = cta - NATT;
    const int f0 = fc * FMAX;
    const int nf = (fc == NFFN - 1) ? (FF - f0) : FMAX;
    const int ndn = nf / 32;
    if (warp == NCW + NEW) {
        uint64_t pol;
        asm volatile("createpolicy.fractional.L2::evict_first.b64 %0, 1.0;" : "=l"(pol));
        if (lane == 0) {
            PROF(0);
            for (int i = 0; i < FSTAGES; i++) { mbar_init(bar_full + 8 * i, 1); mbar_init(bar_empty + 8 * i, NCW + NEW); }
            asm volatile("fence.mbarrier_init.release.cluster;" ::: "memory");
            asm volatile("fence.proxy.async.shared::cta;" ::: "memory");
        }
        __syncthreads();
        int st = 0, ph = 1;
        const uint32_t t0 = (uint32_t)gtime();
        for (int i = 0; i < 16 + ndn; i++) {
            while ((uint32_t)gtime() - t0 < (uint32_t)(i * FFN_TAU)) {}
            mbar_wait(bar_empty + 8 * st, ph);
            const uint32_t dst = sb + st * FSTAGE_BYTES;
            if (i < 16) {
                if (lane == 0) mbar_expect_tx(bar_full + 8 * st, 32 * 2 * nf * 2);
                __syncwarp();
                const size_t off = (size_t)(i * 32 + lane) * FF + f0;
                bulk_load(dst + lane * GU_PITCH, wg + off, nf * 2, bar_full + 8 * st, pol);
                bulk_load(dst + lane * GU_PITCH + FMAX * 2, wu + off, nf * 2, bar_full + 8 * st, pol);
            } else {
                if (lane == 0) mbar_expect_tx(bar_full + 8 * st, 32 * DM * 2);
                __syncwarp();
                bulk_load(dst + lane * DN_PITCH, wd + (size_t)(f0 + (i - 16) * 32 + lane) * DM, DM * 2, bar_full + 8 * st, pol);
            }
            if (++st == FSTAGES) { st = 0; ph ^= 1; }
        }
        return;
    }
    {
        uint32_t* xb = (uint32_t*)(smem + SM_XN);
        float* pre = (float*)(smem + SM_P);
        uint32_t* hb = (uint32_t*)(pre + 2 * 2 * FMAX);
        const uint32_t tag = *(volatile unsigned int*)&g_epoch[cta * 8] + 1;
        if (warp < 2) {
            const uint4 u0 = __ldg((const uint4*)(x + warp * DM) + lane), u1 = __ldg((const uint4*)(x + warp * DM + 256) + lane);
            layernorm_row(u0, u1, xb + warp * 256, lane);
        }
        __syncthreads();
        const int r = lane & 7, mi = lane >> 3;
        const int mt_half = nf / 16;
        int st = 0, ph = 0;
        float acc[6][4];
#pragma unroll
        for (int k = 0; k < 6; k++) { acc[k][0] = acc[k][1] = acc[k][2] = acc[k][3] = 0.f; }
        int cb[6];
#pragma unroll
        for (int k = 0; k < 6; k++) {
            const int mt = warp + 8 * k;
            cb[k] = mt < mt_half ? mt * 32 : (mt < 2 * mt_half ? FMAX * 2 + (mt - mt_half) * 32 : -1);
        }
        for (int i = 0; i < 16; i++) {
            mbar_wait(bar_full + 8 * st, ph);
#pragma unroll
            for (int ks = 0; ks < 2; ks++) {
                const int k0 = i * 32 + ks * 16;
                const uint32_t b0 = g < 2 ? xb[g * 256 + k0 / 2 + t] : 0u, b1 = g < 2 ? xb[g * 256 + k0 / 2 + 4 + t] : 0u;
                const uint32_t rowa = sb + st * FSTAGE_BYTES + (ks * 16 + r + 8 * (mi >> 1)) * GU_PITCH + (mi & 1) * 16;
#pragma unroll
                for (int k = 0; k < 6; k++) {
                    if (cb[k] >= 0) { uint32_t a[4]; ldsm4t(a, rowa + cb[k]); mma16816(acc[k], a, b0, b1); }
                }
            }
            __syncwarp();
            if (lane == 0) mbar_arrive(bar_empty + 8 * st);
            if (++st == FSTAGES) { st = 0; ph ^= 1; }
        }
        if (t == 0) {
#pragma unroll
            for (int k = 0; k < 6; k++) {
                if (cb[k] >= 0) {
                    const int c = cb[k] / 2 + g;
                    pre[c] = acc[k][0]; pre[2 * FMAX + c] = acc[k][1];
                    pre[c + 8] = acc[k][2]; pre[2 * FMAX + c + 8] = acc[k][3];
                }
            }
        }
        named_sync(1, (NCW + NEW) * 32);
#pragma unroll 1
        for (int i = tid; i < nf; i += (NCW + NEW) * 32) {
            const int b = i / (nf / 2), c = 2 * (i % (nf / 2));
            float h[2];
#pragma unroll
            for (int e = 0; e < 2; e++) {
                const float gt = bf16r(pre[b * 2 * FMAX + c + e]), up = bf16r(pre[b * 2 * FMAX + FMAX + c + e]);
                const float ge = bf16r(0.5f * gt * (1.f + tanhf(0.7978845608028654f * (gt + 0.044715f * gt * gt * gt))));
                h[e] = ge * up;
            }
            hb[b * (FMAX / 2) + c / 2] = pack_bf16(h[0], h[1]);
        }
        named_sync(1, (NCW + NEW) * 32);
#pragma unroll
        for (int k = 0; k < 4; k++) { acc[k][0] = acc[k][1] = acc[k][2] = acc[k][3] = 0.f; }
        for (int i = 0; i < ndn; i++) {
            mbar_wait(bar_full + 8 * st, ph);
#pragma unroll
            for (int ks = 0; ks < 2; ks++) {
                const int k0 = i * 32 + ks * 16;
                const uint32_t b0 = g < 2 ? hb[g * (FMAX / 2) + k0 / 2 + t] : 0u, b1 = g < 2 ? hb[g * (FMAX / 2) + k0 / 2 + 4 + t] : 0u;
                const uint32_t rowa = sb + st * FSTAGE_BYTES + (ks * 16 + r + 8 * (mi >> 1)) * DN_PITCH + (mi & 1) * 16 + warp * 128;
#pragma unroll
                for (int k = 0; k < 4; k++) { uint32_t a[4]; ldsm4t(a, rowa + k * 32); mma16816(acc[k], a, b0, b1); }
            }
            __syncwarp();
            if (lane == 0) mbar_arrive(bar_empty + 8 * st);
            if (++st == FSTAGES) { st = 0; ph ^= 1; }
        }
        if (t == 0) {
#pragma unroll
            for (int k = 0; k < 4; k++) {
                const int c = warp * 64 + k * 16 + g;
                st_ll2(&g_ffn[fc][0][c], __float_as_uint(acc[k][0]), tag);
                st_ll2(&g_ffn[fc][1][c], __float_as_uint(acc[k][1]), tag);
                st_ll2(&g_ffn[fc][0][c + 8], __float_as_uint(acc[k][2]), tag);
                st_ll2(&g_ffn[fc][1][c + 8], __float_as_uint(acc[k][3]), tag);
            }
        }
        named_sync(1, (NCW + NEW) * 32);
        if (tid == 0) { g_epoch[cta * 8] = tag; PROF(7); PROF_FLUSH(0x81); }
    }
}

}

extern "C" void kernel_launch(void* const* d_in, const int* in_sizes, int n_in, void* d_out, int out_size) {
    (void)in_sizes; (void)n_in; (void)out_size;
    static bool configured = false;
    if (!configured) {
        cudaFuncSetAttribute(fused_decode_kernel, cudaFuncAttributeMaxDynamicSharedMemorySize, SM_TOTAL);
        configured = true;
    }
    fused_decode_kernel<<<NCTA, NTHREADS, SM_TOTAL>>>(
        (const __nv_bfloat16*)d_in[0], (const __nv_bfloat16*)d_in[1], (const __nv_bfloat16*)d_in[2],
        (const __nv_bfloat16*)d_in[3], (const __nv_bfloat16*)d_in[4], (const __nv_bfloat16*)d_in[6],
        (const __nv_bfloat16*)d_in[7], (const __nv_bfloat16*)d_in[8], (__nv_bfloat16*)d_out);
}
```

```cpp
#include <cuda_runtime.h>
#include <cuda_bf16.h>
#include <stdint.h>

namespace {

constexpr int DM = 512;
constexpr int NH = 32;
constexpr int SK = 8192;
constexpr int DH = 128;
constexpr int FF = 1376;

constexpr int NATT = 128;
constexpr int NFFN = 4;
constexpr int NCTA = NATT + NFFN;
constexpr int NPH = 2 * NH;
constexpr int TK = SK / NATT;
constexpr int TILE_BYTES = TK * DH * 2;
constexpr int NSLOT = 10;
constexpr int DEPTH = 3;
constexpr int NLOAD = 2 * NPH;
constexpr int DS = 16;
constexpr int PSTRIDE = DH / 4 + 2;

constexpr int NCW = 4;
constexpr int NEW = 4;
constexpr int NTHREADS = (NCW + NEW + 1) * 32;

constexpr int FMAX = 352;
constexpr int GU_PITCH = 2 * FMAX * 2 + 16;
constexpr int DN_PITCH = DM * 2 + 16;
constexpr int FSTAGE_BYTES = 32 * GU_PITCH;
constexpr int FSTAGES = 4;

constexpr int P_T = 136;
constexpr int P_W = 4 * P_T + 8;
constexpr int SM_QS = NSLOT * TILE_BYTES;
constexpr int SM_P = SM_QS + NPH * 64 * 4;
constexpr int SM_ML = SM_P + NCW * P_W * 4;
constexpr int SM_CW = SM_ML + 32;
constexpr int SM_XN = SM_CW + (64 + 8 + 32) * 4;
constexpr int SM_RED = SM_XN + 2 * DM * 2;
constexpr int SM_FPRE = FSTAGES * FSTAGE_BYTES;
constexpr int SM_BAR = SM_RED + 8 * 64 * 4;
constexpr int SM_TOTAL = SM_BAR + 64 * 8;
static_assert(SM_FPRE + 2 * 2 * FMAX * 4 + 2 * FMAX * 2 <= SM_XN, "ffn scratch");
static_assert(SM_TOTAL <= 195 * 1024 && SM_TOTAL > 232448 / 2, "one CTA per SM; the 196 KB carve-out leaves enough L1");
static_assert(NCW == 4 && NEW == 4 && TK == 64 && NSLOT % 2 == 0, "lane maps");
static_assert(SM_CW % 16 == 0 && SM_XN % 16 == 0 && SM_P % 16 == 0 && SM_BAR % 8 == 0, "alignment");

constexpr int PACE_TAU = 662, PACE_OFF = 500, LAG1 = 1200, LAG2 = 2000;
constexpr int HP_LATE = 8;
constexpr int FIN0 = 64;
constexpr float LOG2E = 1.4426950408889634f;
constexpr int SPIN_LIMIT = 1 << 22;

__device__ __align__(128) uint2 g_q[NPH * DH / 2];
__device__ __align__(128) uint4 g_part[NPH][NATT][PSTRIDE];
__device__ __align__(128) uint4 g_fin[2][DM / 16][NATT][4];
__device__ __align__(128) uint2 g_ffn[NFFN][2][DM];
__device__ __align__(128) unsigned int g_epoch[NCTA * 8];

__device__ __forceinline__ unsigned long long gtime() {
    unsigned long long t; asm volatile("mov.u64 %0, %globaltimer;" : "=l"(t)); return t;
}

__device__ __forceinline__ float bf16r(float x) { return __bfloat162float(__float2bfloat16_rn(x)); }
__device__ __forceinline__ float bf_lo(uint32_t u) { return __uint_as_float(u << 16); }
__device__ __forceinline__ float bf_hi(uint32_t u) { return __uint_as_float(u & 0xffff0000u); }
__device__ __forceinline__ uint32_t pack_bf16(float lo, float hi) {
    uint32_t r; asm("cvt.rn.bf16x2.f32 %0, %1, %2;" : "=r"(r) : "f"(hi), "f"(lo)); return r;
}
__device__ __forceinline__ float ex2(float x) { float r; asm("ex2.approx.ftz.f32 %0, %1;" : "=f"(r) : "f"(x)); return r; }

__device__ __forceinline__ void mbar_init(uint32_t a, uint32_t c) {
    asm volatile("mbarrier.init.shared::cta.b64 [%0], %1;" ::"r"(a), "r"(c) : "memory");
}
__device__ __forceinline__ void mbar_expect_tx(uint32_t a, uint32_t b) {
    asm volatile("mbarrier.arrive.expect_tx.shared::cta.b64 _, [%0], %1;" ::"r"(a), "r"(b) : "memory");
}
__device__ __forceinline__ void mbar_arrive(uint32_t a) {
    asm volatile("mbarrier.arrive.shared::cta.b64 _, [%0];" ::"r"(a) : "memory");
}
__device__ __forceinline__ void mbar_wait(uint32_t a, uint32_t ph) {
    uint32_t ok; int it = 0;
    do {
        asm volatile("{.reg .pred p; mbarrier.try_wait.parity.shared::cta.b64 p, [%1], %2; selp.u32 %0,1,0,p;}"
                     : "=r"(ok) : "r"(a), "r"(ph) : "memory");
        if (++it > SPIN_LIMIT) __trap();
    } while (!ok);
}
__device__ __forceinline__ bool mbar_test(uint32_t a, uint32_t ph) {
    uint32_t ok;
    asm volatile("{.reg .pred p; mbarrier.test_wait.parity.shared::cta.b64 p, [%1], %2; selp.u32 %0,1,0,p;}"
                 : "=r"(ok) : "r"(a), "r"(ph) : "memory");
    return ok;
}
__device__ __forceinline__ void bulk_load(uint32_t dst, const void* src, uint32_t bytes, uint32_t bar, uint64_t pol) {
    asm volatile("cp.async.bulk.shared::cluster.global.mbarrier::complete_tx::bytes.L2::cache_hint [%0], [%1], %2, [%3], %4;"
                 ::"r"(dst), "l"(src), "r"(bytes), "r"(bar), "l"(pol) : "memory");
}
__device__ __forceinline__ void named_sync(int id, int n) { asm volatile("bar.sync %0, %1;" ::"r"(id), "r"(n) : "memory"); }

__device__ __forceinline__ void ldsm4(uint32_t (&r)[4], uint32_t a) {
    asm volatile("ldmatrix.sync.aligned.m8n8.x4.shared.b16 {%0,%1,%2,%3}, [%4];"
                 : "=r"(r[0]), "=r"(r[1]), "=r"(r[2]), "=r"(r[3]) : "r"(a) : "memory");
}
__device__ __forceinline__ void ldsm4t(uint32_t (&r)[4], uint32_t a) {
    asm volatile("ldmatrix.sync.aligned.m8n8.x4.trans.shared.b16 {%0,%1,%2,%3}, [%4];"
                 : "=r"(r[0]), "=r"(r[1]), "=r"(r[2]), "=r"(r[3]) : "r"(a) : "memory");
}
__device__ __forceinline__ void mma16816(float (&c)[4], const uint32_t (&a)[4], uint32_t b0, uint32_t b1) {
    asm volatile("mma.sync.aligned.m16n8k16.row.col.f32.bf16.bf16.f32 {%0,%1,%2,%3}, {%4,%5,%6,%7}, {%8,%9}, {%0,%1,%2,%3};"
                 : "+f"(c[0]), "+f"(c[1]), "+f"(c[2]), "+f"(c[3])
                 : "r"(a[0]), "r"(a[1]), "r"(a[2]), "r"(a[3]), "r"(b0), "r"(b1));
}

__device__ __forceinline__ void mma16816_z(float (&c)[4], const uint32_t (&a)[4], uint32_t b0, uint32_t b1) {
    asm volatile("mma.sync.aligned.m16n8k16.row.col.f32.bf16.bf16.f32 {%0,%1,%2,%3}, {%4,%5,%6,%7}, {%8,%9}, {%10,%10,%10,%10};"
                 : "=f"(c[0]), "=f"(c[1]), "=f"(c[2]), "=f"(c[3])
                 : "r"(a[0]), "r"(a[1]), "r"(a[2]), "r"(a[3]), "r"(b0), "r"(b1), "f"(0.f));
}

__device__ __forceinline__ uint4 ld_ll(const void* p) {
    uint4 v;
    asm volatile("ld.relaxed.gpu.global.v4.u32 {%0,%1,%2,%3}, [%4];"
                 : "=r"(v.x), "=r"(v.y), "=r"(v.z), "=r"(v.w) : "l"(p) : "memory");
    return v;
}
__device__ __forceinline__ void st_ll2(void* p, uint32_t a, uint32_t tag) {
    asm volatile("st.relaxed.gpu.global.v2.u32 [%0], {%1,%2};" ::"l"(p), "r"(a), "r"(tag) : "memory");
}
__device__ __forceinline__ void st_ll16(void* p, uint32_t a, uint32_t b, uint32_t c, uint32_t tag) {
    asm volatile("{.reg .b128 t; .reg .b64 lo, hi; mov.b64 lo, {%1,%2}; mov.b64 hi, {%3,%4}; mov.b128 t, {lo, hi};\n\t"
                 "st.relaxed.gpu.global.b128 [%0], t;}" ::"l"(p), "r"(a), "r"(b), "r"(c), "r"(tag) : "memory");
}
__device__ __forceinline__ void ld_ll16_missing(uint4& v, const void* p, uint32_t tag) {
    asm volatile("{.reg .pred q; setp.ne.u32 q, %3, %5;\n\t"
                 "@q ld.relaxed.gpu.global.v4.u32 {%0,%1,%2,%3}, [%4];}"
                 : "+r"(v.x), "+r"(v.y), "+r"(v.z), "+r"(v.w) : "l"(p), "r"(tag) : "memory");
}
__device__ __forceinline__ void st_pack4(void* p, float a, float b, float c, float d, uint32_t tag) {
    const uint32_t ua = __float_as_uint(a) + 0x80u, ub = __float_as_uint(b) + 0x80u;
    const uint32_t uc = __float_as_uint(c) + 0x80u, ud = __float_as_uint(d) + 0x80u;
    st_ll16(p, __byte_perm(ua, ub, 0x5321), __byte_perm(ub, uc, 0x6532), __byte_perm(uc, ud, 0x7653), tag);
}
__device__ __forceinline__ void unpack4(const uint4& u, float (&v)[4]) {
    v[0] = __uint_as_float(u.x << 8);
    v[1] = __uint_as_float(__byte_perm(u.x, u.y, 0x5430));
    v[2] = __uint_as_float(__byte_perm(u.y, u.z, 0x4320));
    v[3] = __uint_as_float(u.z);
}
__device__ __forceinline__ void st_u16_if(void* p, uint32_t v, bool on) {
    asm volatile("{.reg .pred q; setp.ne.u32 q, %2, 0; @q st.global.u16 [%0], %1;}" ::"l"(p), "h"((unsigned short)v), "r"((uint32_t)on) : "memory");
}
__device__ __forceinline__ bool ll_ok(const uint4& v, uint32_t tag) { return v.y == tag && v.w == tag; }

__device__ __forceinline__ float warp_max(float v) {
    int i = __float_as_int(v);
    i = i >= 0 ? i : (i ^ 0x7fffffff);
    i = __reduce_max_sync(0xffffffffu, i);
    i = i >= 0 ? i : (i ^ 0x7fffffff);
    return __int_as_float(i);
}

__device__ __forceinline__ float rcp_approx(float x) { float r; asm("rcp.approx.ftz.f32 %0, %1;" : "=f"(r) : "f"(x)); return r; }

__device__ __noinline__ void layernorm_row(uint4 u0, uint4 u1, uint32_t* dst, int lane) {
    uint32_t w[8] = {u0.x, u0.y, u0.z, u0.w, u1.x, u1.y, u1.z, u1.w};
    float y[16];
    float s = 0.f;
#pragma unroll
    for (int i = 0; i < 8; i++) { y[2 * i] = bf_lo(w[i]); y[2 * i + 1] = bf_hi(w[i]); s += y[2 * i] + y[2 * i + 1]; }
#pragma unroll
    for (int o = 16; o > 0; o >>= 1) s += __shfl_xor_sync(0xffffffffu, s, o);
    const float mean = s * (1.f / DM);
    float v = 0.f;
#pragma unroll
    for (int i = 0; i < 16; i++) { const float d = y[i] - mean; v = fmaf(d, d, v); }
#pragma unroll
    for (int o = 16; o > 0; o >>= 1) v += __shfl_xor_sync(0xffffffffu, v, o);
    const float mb = bf16r(mean);
    float sd;
    asm("sqrt.approx.f32 %0, %1;" : "=f"(sd) : "f"(bf16r(bf16r(v * (1.f / DM)) + 1e-5f)));
    const float inv = rcp_approx(bf16r(sd));
#pragma unroll
    for (int i = 0; i < 8; i++) {
        const uint32_t d = pack_bf16(y[2 * i] - mb, y[2 * i + 1] - mb);
        w[i] = pack_bf16(bf_lo(d) * inv, bf_hi(d) * inv);
    }
    *(uint4*)(dst + 4 * lane) = make_uint4(w[0], w[1], w[2], w[3]);
    *(uint4*)(dst + 128 + 4 * lane) = make_uint4(w[4], w[5], w[6], w[7]);
}

__device__ __noinline__ void ffn_cta(const __nv_bfloat16* __restrict__ x, const __nv_bfloat16* __restrict__ wg,
                                     const __nv_bfloat16* __restrict__ wu, const __nv_bfloat16* __restrict__ wd);
__device__ __noinline__ void attn_workers(const __nv_bfloat16* __restrict__ x, const __nv_bfloat16* __restrict__ wq,
                                          const __nv_bfloat16* __restrict__ wo);
__device__ __noinline__ void finalize(const __nv_bfloat16* __restrict__ x, __nv_bfloat16* __restrict__ out);

__global__ void __launch_bounds__(NTHREADS, 1)
fused_decode_kernel(const __nv_bfloat16* __restrict__ x, const __nv_bfloat16* __restrict__ kc,
                    const __nv_bfloat16* __restrict__ vc, const __nv_bfloat16* __restrict__ wq,
                    const __nv_bfloat16* __restrict__ wo, const __nv_bfloat16* __restrict__ wg,
                    const __nv_bfloat16* __restrict__ wu, const __nv_bfloat16* __restrict__ wd,
                    __nv_bfloat16* __restrict__ out, const int tau) {
    extern __shared__ __align__(1024) unsigned char smem[];
    const uint32_t sb = (uint32_t)__cvta_generic_to_shared(smem);
    const int cta = blockIdx.x;
    const uint32_t bar_full = sb + SM_BAR, bar_empty = bar_full + 8 * NSLOT, bar_q = bar_empty + 8 * NSLOT;
    volatile int* progress = (volatile int*)(smem + SM_BAR + 60 * 8);

    if (threadIdx.x < 32 && cta < NATT) {
        uint64_t pol = 0;
        const char* src0 = (const char*)kc + (size_t)cta * TILE_BYTES;
        const char* src1 = (const char*)vc + (size_t)cta * TILE_BYTES;
        uint32_t t0 = 0;
        if (threadIdx.x == 0) {
            t0 = (uint32_t)gtime();
            mbar_init(bar_full, 1);
            asm volatile("fence.mbarrier_init.release.cluster;" ::: "memory");
            asm volatile("fence.proxy.async.shared::cta;" ::: "memory");
            asm volatile("createpolicy.fractional.L2::evict_first.b64 %0, 1.0;" : "=l"(pol));
            mbar_expect_tx(bar_full, TILE_BYTES);
            bulk_load(sb, src0, TILE_BYTES, bar_full, pol);
            { const char* nx = src0 + NATT * TILE_BYTES; src0 = src1; src1 = nx; }
#pragma unroll 1
            for (int i = 1; i < NSLOT; i++) mbar_init(bar_full + 8 * i, 1);
#pragma unroll 1
            for (int i = 0; i < NSLOT; i++) mbar_init(bar_empty + 8 * i, NCW);
            mbar_init(bar_q, 1); mbar_init(bar_q + 8, NEW); mbar_init(bar_q + 16, NEW);
            progress[0] = 0; progress[1] = 0;
            asm volatile("fence.mbarrier_init.release.cluster;" ::: "memory");
            asm volatile("fence.proxy.async.shared::cta;" ::: "memory");
        }
        __syncwarp();
        asm volatile("bar.arrive 0, %0;" ::"n"(NTHREADS) : "memory");
        if (threadIdx.x == 0) {
            int st = 1, ph = 1;
            int ws = 0, wph = 0;
            int landed = 0;
#pragma unroll 1
            for (int i = 1; i < NLOAD; i++) {
                for (int it = 0;; it++) {
                    const int lag = (int)((uint32_t)gtime() - t0) - (i * tau + PACE_OFF);
                    if (lag >= 0 && i - landed < DEPTH + (lag > LAG1) + (lag > LAG2)) break;
                    if (landed < i && mbar_test(bar_full + 8 * ws, wph)) {
                        ++landed;
                        if (++ws == NSLOT) { ws = 0; wph ^= 1; }
                    }
                    if (it > SPIN_LIMIT) __trap();
                }
                mbar_wait(bar_empty + 8 * st, ph);
                mbar_expect_tx(bar_full + 8 * st, TILE_BYTES);
                bulk_load(sb + st * TILE_BYTES, src0, TILE_BYTES, bar_full + 8 * st, pol);
                const char* nx = src0 + NATT * TILE_BYTES; src0 = src1; src1 = nx;
                if (++st == NSLOT) { st = 0; ph ^= 1; }
            }
            progress[1] = 1;
        }
        __syncwarp();
        if (cta >= FIN0 && cta < FIN0 + 64) finalize(x, out);
        return;
    }
    if (cta >= NATT) ffn_cta(x, wg, wu, wd);
    else attn_workers(x, wq, wo);
}

__device__ __noinline__ void attn_workers(const __nv_bfloat16* __restrict__ x, const __nv_bfloat16* __restrict__ wq,
                                          const __nv_bfloat16* __restrict__ wo) {
    extern __shared__ __align__(1024) unsigned char smem[];
    const uint32_t sb = (uint32_t)__cvta_generic_to_shared(smem);
    const int cta = blockIdx.x;
    const uint32_t bar_full = sb + SM_BAR, bar_empty = bar_full + 8 * NSLOT, bar_q = bar_empty + 8 * NSLOT;
    volatile int* progress = (volatile int*)(smem + SM_BAR + 60 * 8);
    {
        const int tid = threadIdx.x - 32, warp = tid >> 5, lane = tid & 31;
        const int g = lane >> 2, t = lane & 3;
        uint32_t* xb = (uint32_t*)(smem + SM_XN);
        float* red = (float*)(smem + SM_RED);
        uint4 wv[8];
        uint4 u0 = make_uint4(0, 0, 0, 0), u1 = u0;
        if (warp < 2) { u0 = __ldg((const uint4*)(x + warp * DM) + lane); u1 = __ldg((const uint4*)(x + warp * DM + 256) + lane); }
        {
            const uint4* src = (const uint4*)(wq + (size_t)(tid >> 2) * (NH * DH) + cta * 32 + (tid & 3) * 8);
#pragma unroll
            for (int i = 0; i < 8; i++) wv[i] = __ldg(src + (size_t)i * 64 * (NH * DH / 8));
        }
        if (warp == NCW) st_ll2(&g_q[(lane >> 4) * 2048 + cta * 16 + (lane & 15)], 0u, 0u);
        uint32_t tag;
        asm volatile("ld.relaxed.gpu.global.u32 %0, [%1];" : "=r"(tag) : "l"(&g_epoch[cta * 8]) : "memory");
        if (warp < 2) layernorm_row(u0, u1, xb + warp * 256, lane);
        named_sync(0, NTHREADS);
        tag += 1;
        if (tid == 0) progress[2] = (int)tag;
        {
            float a0[8], a1[8];
#pragma unroll
            for (int c = 0; c < 8; c++) { a0[c] = 0.f; a1[c] = 0.f; }
#pragma unroll
            for (int i = 0; i < 8; i++) {
                const float x0 = __bfloat162float(((const __nv_bfloat16*)xb)[(tid >> 2) + 64 * i]);
                const float x1 = __bfloat162float(((const __nv_bfloat16*)xb)[DM + (tid >> 2) + 64 * i]);
                const uint32_t w[4] = {wv[i].x, wv[i].y, wv[i].z, wv[i].w};
#pragma unroll
                for (int c = 0; c < 4; c++) {
                    const float lo = bf_lo(w[c]), hi = bf_hi(w[c]);
                    a0[2 * c] = fmaf(x0, lo, a0[2 * c]); a0[2 * c + 1] = fmaf(x0, hi, a0[2 * c + 1]);
                    a1[2 * c] = fmaf(x1, lo, a1[2 * c]); a1[2 * c + 1] = fmaf(x1, hi, a1[2 * c + 1]);
                }
            }
            const bool b4 = lane & 16, b3 = lane & 8, b2 = lane & 4;
            float r8[8], r4[4], r2[2];
#pragma unroll
            for (int c = 0; c < 8; c++) {
                const float keep = b4 ? a1[c] : a0[c], send = b4 ? a0[c] : a1[c];
                r8[c] = keep + __shfl_xor_sync(0xffffffffu, send, 16);
            }
#pragma unroll
            for (int c = 0; c < 4; c++) {
                const float keep = b3 ? r8[4 + c] : r8[c], send = b3 ? r8[c] : r8[4 + c];
                r4[c] = keep + __shfl_xor_sync(0xffffffffu, send, 8);
            }
#pragma unroll
            for (int c = 0; c < 2; c++) {
                const float keep = b2 ? r4[2 + c] : r4[c], send = b2 ? r4[c] : r4[2 + c];
                r2[c] = keep + __shfl_xor_sync(0xffffffffu, send, 4);
            }
            const int col = (b4 ? 32 : 0) + t * 8 + (b3 ? 4 : 0) + (b2 ? 2 : 0);
            *(float2*)&red[warp * 64 + col] = make_float2(r2[0], r2[1]);
        }
        named_sync(1, (NCW + NEW) * 32);

        if (warp < NCW) {
            const int r = lane & 7, mi = lane >> 3;
            uint32_t koff[4], voff[4];
#pragma unroll
            for (int j = 0; j < 4; j++) {
                koff[j] = sb + (warp * 16 + r + 8 * (mi & 1)) * 256 + (((2 * j + (mi >> 1)) ^ r) << 4);
                voff[j] = sb + (warp * 16 + r + 8 * (mi >> 1)) * 256 + (((2 * j + (mi & 1)) ^ r) << 4);
            }
            const bool owner = (t == (g >> 1));
            const bool odd = g & 1;
            const uint32_t* qs = (const uint32_t*)(smem + SM_QS);
            float* P = (float*)(smem + SM_P);
            float* ml = (float*)(smem + SM_ML);
            uint4* rec = &g_part[0][cta][0];
            int st = 0, ph = 0;
            mbar_wait(bar_q, 0);
#pragma unroll 1
            for (int p = 0; p < NPH; p++) {
                if (p == 1) mbar_wait(bar_q + 8, 0);
                if (p == 8) mbar_wait(bar_q + 16, 0);
                uint32_t qb[8][2], a[8][4];
#pragma unroll
                for (int k = 0; k < 8; k++) {
                    qb[k][0] = qs[p * 64 + (((2 * k) ^ g) << 2) + t];
                    qb[k][1] = qs[p * 64 + (((2 * k + 1) ^ g) << 2) + t];
                }
                mbar_wait(bar_full + 8 * st, ph);
                if (lane == 0 && p > 0) mbar_arrive(bar_empty + 8 * ((st == 0 ? NSLOT : st) - 1));
                {
                    const uint32_t so = st * TILE_BYTES;
#pragma unroll
                    for (int k = 0; k < 8; k++) ldsm4(a[k], koff[k & 3] + so + (k >> 2) * 128);
                }
                float c0[4], c1[4];
                mma16816_z(c0, a[0], qb[0][0], qb[0][1]);
                mma16816_z(c1, a[1], qb[1][0], qb[1][1]);
#pragma unroll
                for (int k = 2; k < 8; k += 2) {
                    mma16816(c0, a[k], qb[k][0], qb[k][1]);
                    mma16816(c1, a[k + 1], qb[k + 1][0], qb[k + 1][1]);
                }
                ++st;
                float s0 = odd ? (c0[1] + c1[1]) : (c0[0] + c1[0]);
                float s1 = odd ? (c0[3] + c1[3]) : (c0[2] + c1[2]);
                s0 = bf16r(bf16r(s0) * 0.08838834764831845f);
                s1 = bf16r(bf16r(s1) * 0.08838834764831845f);
                if (!owner) { s0 = -INFINITY; s1 = -INFINITY; }
                const float mw = warp_max(fmaxf(s0, s1));
                float l = ex2((s0 - mw) * LOG2E) + ex2((s1 - mw) * LOG2E);
#pragma unroll
                for (int o = 16; o > 0; o >>= 1) l += __shfl_xor_sync(0xffffffffu, l, o);
                if (lane == 0) *(float2*)&ml[2 * warp] = make_float2(mw, l);
                named_sync(2, NCW * 32);
                const float4 ma = *(const float4*)ml, mb = *(const float4*)(ml + 4);
                const float M = fmaxf(fmaxf(ma.x, ma.z), fmaxf(mb.x, mb.z));
                if (warp == 0) {
                    const float L = (ex2((ma.x - M) * LOG2E) * ma.y + ex2((ma.z - M) * LOG2E) * ma.w) +
                                    (ex2((mb.x - M) * LOG2E) * mb.y + ex2((mb.z - M) * LOG2E) * mb.w);
                    if (lane < 2) st_ll16(rec + DH / 4 + lane, __float_as_uint(M), __float_as_uint(L), 0u, tag);
                }
                const float p0 = ex2((s0 - M) * LOG2E), p1 = ex2((s1 - M) * LOG2E);
                const uint32_t b0 = odd ? pack_bf16(0.f, p0) : pack_bf16(p0, 0.f);
                const uint32_t b1 = odd ? pack_bf16(0.f, p1) : pack_bf16(p1, 0.f);
                if (p == NPH - 6) {
#pragma unroll
                    for (int h = NPH - 2; h < NPH; h++) {
                        if (t == 0) st_ll16(&g_part[h][cta][tid >> 2], 0u, 0u, 0u, 0u);
                        if (tid < 2) st_ll16(&g_part[h][cta][DH / 4 + tid], 0u, 0u, 0u, 0u);
                    }
                }
                mbar_wait(bar_full + 8 * st, ph);
                if (lane == 0) mbar_arrive(bar_empty + 8 * (st - 1));
                {
                    const uint32_t so = st * TILE_BYTES;
#pragma unroll
                    for (int k = 0; k < 8; k++) ldsm4t(a[k], voff[k & 3] + so + (k >> 2) * 128);
                }
                float* Pw = P + warp * P_W + t * P_T + g;
#pragma unroll
                for (int k = 0; k < 8; k++) {
                    float acc[4];
                    mma16816_z(acc, a[k], b0, b1);
                    Pw[((k ^ t) * 2) * 8] = acc[0] + acc[3];
                    Pw[((k ^ t) * 2 + 1) * 8] = acc[2] + acc[1];
                }
                if (++st == NSLOT) { st = 0; ph ^= 1; }
                named_sync(2, NCW * 32);
                {
                    const float* Pr = P + t * P_W + (tid >> 2) * 4;
                    const float4 q0 = *(const float4*)Pr, q1 = *(const float4*)(Pr + P_T);
                    const float4 q2 = *(const float4*)(Pr + 2 * P_T), q3 = *(const float4*)(Pr + 3 * P_T);
                    float o[4] = {(q0.x + q1.x) + (q2.x + q3.x), (q0.y + q1.y) + (q2.y + q3.y),
                                  (q0.z + q1.z) + (q2.z + q3.z), (q0.w + q1.w) + (q2.w + q3.w)};
#pragma unroll
                    for (int k = 1; k < 4; k <<= 1) {
#pragma unroll
                        for (int i = 0; i < 4; i++) o[i] += __shfl_xor_sync(0xffffffffu, o[i], k);
                    }
                    if (t == 0) st_pack4(rec + (tid >> 2), o[0], o[1], o[2], o[3], tag);
                }
                if (tid == 0) *progress = p + 1;
                rec += NATT * PSTRIDE;
            }
            asm volatile("exit;");
        }

        const int et = tid - NCW * 32, ew = warp - NCW;
        if (ew == 0) {
            float2 s = make_float2(0.f, 0.f);
#pragma unroll
            for (int w = 0; w < NCW + NEW; w++) { const float2 v = *(const float2*)&red[w * 64 + 2 * lane]; s.x += v.x; s.y += v.y; }
            st_ll2(&g_q[(lane >> 4) * 2048 + cta * 16 + (lane & 15)], pack_bf16(s.x, s.y), tag);
        }
        {
            uint32_t* qs = (uint32_t*)(smem + SM_QS);
            if (ew == 1) {
                uint4 v; int it = 0;
                do { v = ld_ll(&g_q[2 * lane]); if (++it > SPIN_LIMIT) __trap(); } while (!ll_ok(v, tag));
                *(uint2*)&qs[2 * lane] = make_uint2(v.x, v.z);
                __syncwarp();
                if (lane == 0) mbar_arrive(bar_q);
            }
            mbar_wait(bar_q, 0);
#pragma unroll 1
            for (int bt = 0; bt < 3; bt++) {
                const int w0 = (bt == 0 ? 32 : 288 + (bt - 1) * 896) + et;
                const int n = bt == 0 ? 2 : 7;
                uint4 v[7]; int it = 0;
                while (true) {
                    bool ok = true;
#pragma unroll
                    for (int i = 0; i < 7; i++)
                        if (i < n && w0 + i * 128 < NPH * 32) v[i] = ld_ll(&g_q[2 * (w0 + i * 128)]);
#pragma unroll
                    for (int i = 0; i < 7; i++)
                        if (i < n && w0 + i * 128 < NPH * 32) ok = ok && ll_ok(v[i], tag);
                    if (__all_sync(0xffffffffu, ok)) break;
                    if (++it > SPIN_LIMIT) __trap();
                    __nanosleep(300);
                }
#pragma unroll
                for (int i = 0; i < 7; i++)
                    if (i < n && w0 + i * 128 < NPH * 32) *(uint2*)&qs[2 * (w0 + i * 128)] = make_uint2(v[i].x, v[i].z);
                __syncwarp();
                if (bt != 1 && lane == 0) mbar_arrive(bar_q + 8 + 4 * bt);
            }
        }
        float* cw = (float*)(smem + SM_CW);
        float* mwl = cw + 64;
        float* o0 = cw + 72;
        const int hp = cta >> 3, rs = cta & 7;
        float sacc[2][4] = {{0.f, 0.f, 0.f, 0.f}, {0.f, 0.f, 0.f, 0.f}};
#pragma unroll 1
        for (int job = 0; job < 4; job++) {
            const int p = hp + 16 * job;
            const bool last = (job == 3);
            const int need = min(p + 3, NPH - 1);
            {
                int it = 0;
                while (*progress < need - 2) { __nanosleep(500); if (++it > SPIN_LIMIT) __trap(); }
            }
            const bool late = last && hp < HP_LATE;
            const uint2* wsrc = (const uint2*)(wo + (size_t)((p - NH) * DH + rs * DS) * DM) + et;
            uint2 wr[DS];
#pragma unroll
            for (int i = 0; i < DS; i++) wr[i] = make_uint2(0u, 0u);
            if (job >= 2 && !late) {
#pragma unroll
                for (int i = 0; i < DS; i++) wr[i] = __ldg(wsrc + i * (DM / 4));
            }
            if (job == 1 && ew == 0 && lane < 8) g_epoch[cta * 8 + lane] = tag;
            uint4* dst_fin = &g_fin[0][et >> 2][cta][et & 3];
            if (job == 2) {
                st_ll16(dst_fin, 0u, 0u, 0u, 0u);
                st_ll16(dst_fin + (DM / 16) * NATT * 4, 0u, 0u, 0u, 0u);
            }
            float wf[DS][4];
#pragma unroll
            for (int i = 0; i < DS; i++) {
                wf[i][0] = bf_lo(wr[i].x); wf[i][1] = bf_hi(wr[i].x); wf[i][2] = bf_lo(wr[i].y); wf[i][3] = bf_hi(wr[i].y);
                const float o = job >= 2 ? o0[(job & 1) * 16 + i] : 0.f;
#pragma unroll
                for (int c = 0; c < 4; c++) sacc[0][c] = fmaf(o, wf[i][c], sacc[0][c]);
                asm volatile("" : "+f"(wf[i][0]), "+f"(wf[i][1]), "+f"(wf[i][2]), "+f"(wf[i][3]));
            }
            if (last && !late) st_pack4(dst_fin, sacc[0][0], sacc[0][1], sacc[0][2], sacc[0][3], tag);
            {
                int it = 0;
                while (*progress < need) { __nanosleep(100); if (++it > SPIN_LIMIT) __trap(); }
            }
            const uint4* src = &g_part[p][ew * 32 + g][0];
            uint4 uo[4], um[4];
#pragma unroll
            for (int i = 0; i < 4; i++) { uo[i] = make_uint4(0u, 0u, 0u, 0u); um[i] = uo[i]; }
            {
                int it = 0;
                while (true) {
#pragma unroll
                    for (int i = 0; i < 4; i++) ld_ll16_missing(um[i], src + i * 8 * PSTRIDE + DH / 4, tag);
#pragma unroll
                    for (int i = 0; i < 4; i++) ld_ll16_missing(uo[i], src + i * 8 * PSTRIDE + rs * 4 + t, tag);
                    const uint32_t bad = ((um[0].w ^ tag) | (um[1].w ^ tag)) | ((um[2].w ^ tag) | (um[3].w ^ tag));
                    if (!__any_sync(0xffffffffu, bad != 0)) break;
                    if (++it > SPIN_LIMIT) __trap();
                    if (p < NPH - 2) __nanosleep(300);
                }
            }
            float sc[4];
            {
                const float mx = warp_max(fmaxf(fmaxf(__uint_as_float(um[0].x), __uint_as_float(um[1].x)),
                                                fmaxf(__uint_as_float(um[2].x), __uint_as_float(um[3].x))));
                if (lane == 0) mwl[ew] = mx;
                named_sync(3, NEW * 32);
                const float4 m4 = *(const float4*)mwl;
                const float M = fmaxf(fmaxf(m4.x, m4.y), fmaxf(m4.z, m4.w));
                float L = 0.f;
#pragma unroll
                for (int i = 0; i < 4; i++) { sc[i] = ex2((__uint_as_float(um[i].x) - M) * LOG2E); L = fmaf(sc[i], __uint_as_float(um[i].y), L); }
#pragma unroll
                for (int o = 4; o < 32; o <<= 1) L += __shfl_xor_sync(0xffffffffu, L, o);
                if (lane == 0) mwl[4 + ew] = L;
            }
            {
                int it = 0;
                while (true) {
                    const uint32_t bad = ((uo[0].w ^ tag) | (uo[1].w ^ tag)) | ((uo[2].w ^ tag) | (uo[3].w ^ tag));
                    if (!__any_sync(0xffffffffu, bad != 0)) break;
                    if (++it > SPIN_LIMIT) __trap();
                    if (p < NPH - 2) __nanosleep(300);
#pragma unroll
                    for (int i = 0; i < 4; i++) ld_ll16_missing(uo[i], src + i * 8 * PSTRIDE + rs * 4 + t, tag);
                }
            }
            {
                float v[4] = {0.f, 0.f, 0.f, 0.f};
#pragma unroll
                for (int i = 0; i < 4; i++) {
                    float u[4];
                    unpack4(uo[i], u);
#pragma unroll
                    for (int c = 0; c < 4; c++) v[c] = fmaf(sc[i], u[c], v[c]);
                }
#pragma unroll
                for (int o = 4; o < 32; o <<= 1) {
#pragma unroll
                    for (int c = 0; c < 4; c++) v[c] += __shfl_xor_sync(0xffffffffu, v[c], o);
                }
                if (lane < 4) *(float4*)&cw[ew * 16 + lane * 4] = make_float4(v[0], v[1], v[2], v[3]);
            }
            named_sync(3, NEW * 32);
            if (late) {
                int it = 0;
                while (progress[1] == 0) { __nanosleep(100); if (++it > SPIN_LIMIT) __trap(); }
#pragma unroll
                for (int i = 0; i < DS; i++) wr[i] = __ldg(wsrc + i * (DM / 4));
#pragma unroll
                for (int i = 0; i < DS; i++) {
                    wf[i][0] = bf_lo(wr[i].x); wf[i][1] = bf_hi(wr[i].x); wf[i][2] = bf_lo(wr[i].y); wf[i][3] = bf_hi(wr[i].y);
                    const float o = o0[16 + i];
#pragma unroll
                    for (int c = 0; c < 4; c++) sacc[0][c] = fmaf(o, wf[i][c], sacc[0][c]);
                }
                st_pack4(dst_fin, sacc[0][0], sacc[0][1], sacc[0][2], sacc[0][3], tag);
            }
            {
                const int i16 = lane & 15;
                const float ov = (cw[i16] + cw[16 + i16]) + (cw[32 + i16] + cw[48 + i16]);
                const float4 l4 = *(const float4*)(mwl + 4);
                const float inv = rcp_approx((l4.x + l4.y) + (l4.z + l4.w));
                float y[4] = {0.f, 0.f, 0.f, 0.f};
#pragma unroll
                for (int i = 0; i < DS; i++) {
                    const float o = __shfl_sync(0xffffffffu, ov, i);
#pragma unroll
                    for (int c = 0; c < 4; c++) y[c] = fmaf(o, wf[i][c], y[c]);
                }
#pragma unroll
                for (int c = 0; c < 4; c++) sacc[1][c] = fmaf(y[c], inv, sacc[1][c]);
                if (last) st_pack4(dst_fin + (DM / 16) * NATT * 4, sacc[1][0], sacc[1][1], sacc[1][2], sacc[1][3], tag);
                if (job < 2 && et < 16) o0[job * 16 + et] = bf16r(ov * inv);
            }
        }
        asm volatile("exit;");
    }
}

__device__ __noinline__ void finalize(const __nv_bfloat16* __restrict__ x, __nv_bfloat16* __restrict__ out) {
    extern __shared__ __align__(1024) unsigned char smem[];
    volatile int* progress = (volatile int*)(smem + SM_BAR + 60 * 8);
    const int lane = threadIdx.x, fi = blockIdx.x - FIN0;
    const uint32_t tag = (uint32_t)progress[2];
    const int fb = fi >> 5, cg = fi & 31;
    const int fcol = cg * 16 + (lane & 3) * 4 + ((lane >> 1) & 2) + ((lane >> 3) & 1);
    float gate, xres;
    {
        uint2 v0, v1; int it = 0;
        while (true) {
            const uint2* src = &g_ffn[(lane >> 4) * 2][fb][fcol];
            asm volatile("ld.relaxed.gpu.global.v2.u32 {%0,%1}, [%2];" : "=r"(v0.x), "=r"(v0.y) : "l"(src) : "memory");
            asm volatile("ld.relaxed.gpu.global.v2.u32 {%0,%1}, [%2];" : "=r"(v1.x), "=r"(v1.y) : "l"(src + 2 * DM) : "memory");
            if (!__any_sync(0xffffffffu, v0.y != tag || v1.y != tag)) break;
            if (++it > SPIN_LIMIT) __trap();
            __nanosleep(500);
        }
        float f = __uint_as_float(v0.x) + __uint_as_float(v1.x);
        f += __shfl_xor_sync(0xffffffffu, f, 16);
        f = bf16r(f);
        gate = bf16r(f * rcp_approx(1.f + ex2(-f * LOG2E)));
        xres = __bfloat162float(x[fb * DM + fcol]);
    }
    const uint4* src = &g_fin[fb][cg][0][0] + lane;
    float a[4] = {0.f, 0.f, 0.f, 0.f};
#pragma unroll 1
    for (int pass = 0; pass < 3; pass++) {
        constexpr int NA = 15;
        uint4 u[NA];
#pragma unroll
        for (int i = 0; i < NA; i++) u[i] = make_uint4(0u, 0u, 0u, (pass == 1 || (pass == 2 && i == 0)) ? 0u : tag);
        for (int it = 0;; it++) {
            ld_ll16_missing(u[0], src, tag);
            uint32_t bad = 0;
            if (pass != 2) {
#pragma unroll
                for (int i = 1; i < NA; i++) ld_ll16_missing(u[i], src + i * 32, tag);
#pragma unroll
                for (int i = 1; i < NA; i++) bad |= u[i].w ^ tag;
            }
            bad |= u[0].w ^ tag;
            if (!__any_sync(0xffffffffu, bad != 0)) break;
            if (it > SPIN_LIMIT) __trap();
            if (*progress < NPH) __nanosleep(200);
        }
        float e[4], f[4];
        unpack4(u[0], e);
#pragma unroll
        for (int c = 0; c < 4; c++) a[c] += e[c];
        if (pass != 2) {
#pragma unroll
            for (int i = 1; i < NA; i += 2) {
                unpack4(u[i], e); unpack4(u[i + 1], f);
#pragma unroll
                for (int c = 0; c < 4; c++) a[c] += e[c] + f[c];
            }
        }
        if (pass == 1) src += NA * 32;
        const bool h1 = lane & 4, h2 = lane & 8;
        const float e0 = (h1 ? a[2] : a[0]) + __shfl_xor_sync(0xffffffffu, h1 ? a[0] : a[2], 4);
        const float e1 = (h1 ? a[3] : a[1]) + __shfl_xor_sync(0xffffffffu, h1 ? a[1] : a[3], 4);
        float sv = (h2 ? e1 : e0) + __shfl_xor_sync(0xffffffffu, h2 ? e0 : e1, 8);
        sv += __shfl_xor_sync(0xffffffffu, sv, 16);
        st_u16_if(out + fb * DM + fcol, pack_bf16(xres + bf16r(bf16r(sv) * gate), 0.f), pass == 2 && lane < 16);
    }
    asm volatile("exit;");
}

__device__ __noinline__ void ffn_cta(const __nv_bfloat16* __restrict__ x, const __nv_bfloat16* __restrict__ wg,
                                     const __nv_bfloat16* __restrict__ wu, const __nv_bfloat16* __restrict__ wd) {
    extern __shared__ __align__(1024) unsigned char smem[];
    const uint32_t sb = (uint32_t)__cvta_generic_to_shared(smem);
    const int tid = threadIdx.x, warp = tid >> 5, lane = tid & 31;
    const int cta = blockIdx.x;
    const int g = lane >> 2, t = lane & 3;
    const uint32_t bar_full = sb + SM_BAR, bar_empty = bar_full + 8 * NSLOT;
    const int fc = cta - NATT;
    const int f0 = fc * FMAX;
    const int nf = (fc == NFFN - 1) ? (FF - f0) : FMAX;
    const int ndn = nf / 32;
    if (warp == NCW + NEW) {
        uint64_t pol;
        asm volatile("createpolicy.fractional.L2::evict_first.b64 %0, 1.0;" : "=l"(pol));
        if (lane == 0) {
            for (int i = 0; i < FSTAGES; i++) { mbar_init(bar_full + 8 * i, 1); mbar_init(bar_empty + 8 * i, NCW + NEW); }
            asm volatile("fence.mbarrier_init.release.cluster;" ::: "memory");
            asm volatile("fence.proxy.async.shared::cta;" ::: "memory");
        }
        __syncthreads();
        int st = 0, ph = 1;
        for (int i = 0; i < 16 + ndn; i++) {
            mbar_wait(bar_empty + 8 * st, ph);
            const uint32_t dst = sb + st * FSTAGE_BYTES;
            if (i < 16) {
                if (lane == 0) mbar_expect_tx(bar_full + 8 * st, 32 * 2 * nf * 2);
                __syncwarp();
                const size_t off = (size_t)(i * 32 + lane) * FF + f0;
                bulk_load(dst + lane * GU_PITCH, wg + off, nf * 2, bar_full + 8 * st, pol);
                bulk_load(dst + lane * GU_PITCH + FMAX * 2, wu + off, nf * 2, bar_full + 8 * st, pol);
            } else {
                if (lane == 0) mbar_expect_tx(bar_full + 8 * st, 32 * DM * 2);
                __syncwarp();
                bulk_load(dst + lane * DN_PITCH, wd + (size_t)(f0 + (i - 16) * 32 + lane) * DM, DM * 2, bar_full + 8 * st, pol);
            }
            if (++st == FSTAGES) { st = 0; ph ^= 1; }
        }
        return;
    }
    {
        uint32_t* xb = (uint32_t*)(smem + SM_XN);
        float* pre = (float*)(smem + SM_FPRE);
        uint32_t* hb = (uint32_t*)(pre + 2 * 2 * FMAX);
        const uint32_t tag = *(volatile unsigned int*)&g_epoch[cta * 8] + 1;
        if (warp < 2) {
            const uint4 u0 = __ldg((const uint4*)(x + warp * DM) + lane), u1 = __ldg((const uint4*)(x + warp * DM + 256) + lane);
            layernorm_row(u0, u1, xb + warp * 256, lane);
        }
        __syncthreads();
        const int r = lane & 7, mi = lane >> 3;
        const int mt_half = nf / 16;
        int st = 0, ph = 0;
        float acc[6][4];
#pragma unroll
        for (int k = 0; k < 6; k++) { acc[k][0] = acc[k][1] = acc[k][2] = acc[k][3] = 0.f; }
        int cb[6];
#pragma unroll
        for (int k = 0; k < 6; k++) {
            const int mt = warp + 8 * k;
            cb[k] = mt < mt_half ? mt * 32 : (mt < 2 * mt_half ? FMAX * 2 + (mt - mt_half) * 32 : -1);
        }
        for (int i = 0; i < 16; i++) {
            mbar_wait(bar_full + 8 * st, ph);
            if (lane == 0 && i > 0) mbar_arrive(bar_empty + 8 * ((st + FSTAGES - 1) % FSTAGES));
#pragma unroll
            for (int ks = 0; ks < 2; ks++) {
                const int k0 = i * 32 + ks * 16;
                const uint32_t b0 = g < 2 ? xb[g * 256 + k0 / 2 + t] : 0u, b1 = g < 2 ? xb[g * 256 + k0 / 2 + 4 + t] : 0u;
                const uint32_t rowa = sb + st * FSTAGE_BYTES + (ks * 16 + r + 8 * (mi >> 1)) * GU_PITCH + (mi & 1) * 16;
#pragma unroll
                for (int k = 0; k < 6; k++) {
                    if (cb[k] >= 0) { uint32_t a[4]; ldsm4t(a, rowa + cb[k]); mma16816(acc[k], a, b0, b1); }
                }
            }
            if (++st == FSTAGES) { st = 0; ph ^= 1; }
        }
        if (t == 0) {
#pragma unroll
            for (int k = 0; k < 6; k++) {
                if (cb[k] >= 0) {
                    const int c = cb[k] / 2 + g;
                    pre[c] = acc[k][0]; pre[2 * FMAX + c] = acc[k][1];
                    pre[c + 8] = acc[k][2]; pre[2 * FMAX + c + 8] = acc[k][3];
                }
            }
        }
        named_sync(1, (NCW + NEW) * 32);
#pragma unroll 1
        for (int i = tid; i < nf; i += (NCW + NEW) * 32) {
            const int b = i / (nf / 2), c = 2 * (i % (nf / 2));
            float h[2];
#pragma unroll
            for (int e = 0; e < 2; e++) {
                const float gt = bf16r(pre[b * 2 * FMAX + c + e]), up = bf16r(pre[b * 2 * FMAX + FMAX + c + e]);
                const float ge = bf16r(0.5f * gt * (1.f + tanhf(0.7978845608028654f * (gt + 0.044715f * gt * gt * gt))));
                h[e] = ge * up;
            }
            hb[b * (FMAX / 2) + c / 2] = pack_bf16(h[0], h[1]);
        }
        named_sync(1, (NCW + NEW) * 32);
#pragma unroll
        for (int k = 0; k < 4; k++) { acc[k][0] = acc[k][1] = acc[k][2] = acc[k][3] = 0.f; }
        for (int i = 0; i < ndn; i++) {
            mbar_wait(bar_full + 8 * st, ph);
            if (lane == 0) mbar_arrive(bar_empty + 8 * ((st + FSTAGES - 1) % FSTAGES));
#pragma unroll
            for (int ks = 0; ks < 2; ks++) {
                const int k0 = i * 32 + ks * 16;
                const uint32_t b0 = g < 2 ? hb[g * (FMAX / 2) + k0 / 2 + t] : 0u, b1 = g < 2 ? hb[g * (FMAX / 2) + k0 / 2 + 4 + t] : 0u;
                const uint32_t rowa = sb + st * FSTAGE_BYTES + (ks * 16 + r + 8 * (mi >> 1)) * DN_PITCH + (mi & 1) * 16 + warp * 128;
#pragma unroll
                for (int k = 0; k < 4; k++) { uint32_t a[4]; ldsm4t(a, rowa + k * 32); mma16816(acc[k], a, b0, b1); }
            }
            if (++st == FSTAGES) { st = 0; ph ^= 1; }
        }
        if (t == 0) {
#pragma unroll
            for (int k = 0; k < 4; k++) {
                const int c = warp * 64 + k * 16 + g;
                st_ll2(&g_ffn[fc][0][c], __float_as_uint(acc[k][0]), tag);
                st_ll2(&g_ffn[fc][1][c], __float_as_uint(acc[k][1]), tag);
                st_ll2(&g_ffn[fc][0][c + 8], __float_as_uint(acc[k][2]), tag);
                st_ll2(&g_ffn[fc][1][c + 8], __float_as_uint(acc[k][3]), tag);
            }
        }
        named_sync(1, (NCW + NEW) * 32);
        if (tid == 0) g_epoch[cta * 8] = tag;
    }
}

}

extern "C" void kernel_launch(void* const* d_in, const int* in_sizes, int n_in, void* d_out, int out_size) {
    (void)in_sizes; (void)n_in; (void)out_size;
    static int tau = -1;
    if (tau < 0) {
        cudaFuncSetAttribute(fused_decode_kernel, cudaFuncAttributeMaxDynamicSharedMemorySize, SM_TOTAL);
        int dev = 0, khz = 0, bits = 0;
        cudaGetDevice(&dev);
        cudaDeviceGetAttribute(&khz, cudaDevAttrMemoryClockRate, dev);
        cudaDeviceGetAttribute(&bits, cudaDevAttrGlobalMemoryBusWidth, dev);
        const double peak = 2.0 * khz * (bits / 8) * 1e-6;
        tau = peak > 1.0 ? (int)(PACE_TAU * 3352.32 / peak + 0.5) : 0;
        (void)cudaGetLastError();
    }
    fused_decode_kernel<<<NCTA, NTHREADS, SM_TOTAL>>>(
        (const __nv_bfloat16*)d_in[0], (const __nv_bfloat16*)d_in[1], (const __nv_bfloat16*)d_in[2],
        (const __nv_bfloat16*)d_in[3], (const __nv_bfloat16*)d_in[4], (const __nv_bfloat16*)d_in[6],
        (const __nv_bfloat16*)d_in[7], (const __nv_bfloat16*)d_in[8], (__nv_bfloat16*)d_out, tau);
}
```
